```python
import torch

def _softmax(x, axis=-1):
    return torch.softmax(x, dim=axis)

def _gelu(x):
    return torch.nn.functional.gelu(x, approximate='tanh')

def _silu(x):
    return torch.nn.functional.silu(x)

def _sigmoid(x):
    return torch.sigmoid(x)

def _layernorm(x, axis=-1, eps=1e-05):
    m = x.mean(dim=axis, keepdim=True)
    v = x.var(dim=axis, keepdim=True, unbiased=False)
    return (x - m) / torch.sqrt(v + eps)

def _scatter_add(tgt, idx, src, axis=0):
    return tgt.clone().index_add_(axis, idx, src)

def _segment_sum(src, seg, n):
    out = torch.zeros((n,) + src.shape[1:], dtype=src.dtype)
    return out.index_add_(0, seg, src)

def _pad(x, pw):
    flat = tuple((v for pair in reversed(pw) for v in pair))
    return torch.nn.functional.pad(x, flat)
kernel_name = 'parallel_sum__memory_aug_recurrent_mem_tr__moe_arch_mod__prompt'

def setup_inputs():

    _w = lambda a: (lambda t: t.to(torch.bfloat16) if t.is_floating_point() else t)(torch.as_tensor(a))

    def _A_setup():
        B, S, Dm = (1, 2048, 1024)
        H, Dh = (32, 128)
        M, seg = (8, 32)
        seg = min(seg, S)
        S = S // seg * seg
        return {'x': _w((lambda *s: torch.randn(*s, dtype=torch.bfloat16) * 0.05)(B, S, Dm)), 'mem0': _w((lambda *s: torch.randn(*s, dtype=torch.bfloat16) * 1.6)(B, M, Dm)), 'Wq': _w((lambda *s: torch.randn(*s, dtype=torch.bfloat16) * 0.8)(Dm, H, Dh) * Dm ** (-0.5)), 'Wk': _w((lambda *s: torch.randn(*s, dtype=torch.bfloat16) * 0.8)(Dm, H, Dh) * Dm ** (-0.5)), 'Wv': _w((lambda *s: torch.randn(*s, dtype=torch.bfloat16) * 1.6)(Dm, H, Dh) * Dm ** (-0.5)), 'Wo': _w((lambda *s: torch.randn(*s, dtype=torch.bfloat16) * 1.6)(H, Dh, Dm) * (H * Dh) ** (-0.5)), 'seg_len': seg}
    _A_in = _A_setup()

    def _B_setup():
        B, S, D, F, C = (1, 2048, 1024, 3584, 2)
        return {'x': _w((lambda *s: torch.randn(*s, dtype=torch.bfloat16) * 0.05)(B, S, D)), 'w_r': _w((lambda *s: torch.randn(*s, dtype=torch.bfloat16) * 0.05)(D)), 'w_gate': _w((lambda *s: torch.randn(*s, dtype=torch.bfloat16) * 0.05)(D, F)), 'w_up': _w((lambda *s: torch.randn(*s, dtype=torch.bfloat16) * 0.05)(D, F)), 'w_down': _w((lambda *s: torch.randn(*s, dtype=torch.bfloat16) * 0.05)(F, D))}
    _B_in = _B_setup()
    return {'A_x': _A_in['x'], 'A_mem0': _A_in['mem0'], 'A_Wq': _A_in['Wq'], 'A_Wk': _A_in['Wk'], 'A_Wv': _A_in['Wv'], 'A_Wo': _A_in['Wo'], 'A_seg_len': _A_in['seg_len'], 'B_x': _B_in['x'], 'B_w_r': _B_in['w_r'], 'B_w_gate': _B_in['w_gate'], 'B_w_up': _B_in['w_up'], 'B_w_down': _B_in['w_down']}

def reference(A_x, A_mem0, A_Wq, A_Wk, A_Wv, A_Wo, A_seg_len, B_x, B_w_r, B_w_gate, B_w_up, B_w_down):

    def _A_ref(x, mem0, Wq, Wk, Wv, Wo, seg_len):
        B, S, Dm = x.shape
        H, Dh = (Wq.shape[1], Wq.shape[2])
        M = mem0.shape[1]
        scale = Dh ** (-0.5)
        n_seg = S // seg_len
        L = M + seg_len
        idx = torch.arange(L)
        mask = (idx[:, None] < M) | (idx[:, None] >= idx[None, :])
        mem = mem0
        outs = []
        for s in range(n_seg):
            xs = x[:, s * seg_len:(s + 1) * seg_len, :].clone()
            h = torch.concatenate([mem, xs], axis=1)
            q = torch.einsum('btd,dhe->bhte', h, Wq)
            k = torch.einsum('btd,dhe->bhte', h, Wk)
            v = torch.einsum('btd,dhe->bhte', h, Wv)
            scores = torch.einsum('bhqe,bhke->bhqk', q, k) * scale
            scores = torch.where(mask[None, None], scores, -1000000000.0)
            p = _softmax(scores, axis=-1)
            o = torch.einsum('bhqk,bhke->bhqe', p, v)
            o = torch.einsum('bhte,hed->btd', o, Wo)
            mem = o[:, :M, :].clone()
            outs.append(o[:, M:, :])
        return torch.concatenate(outs, axis=1)

    def _B_ref(x, w_r, w_gate, w_up, w_down):
        B, S, D = x.shape
        C = 2
        r = x @ w_r
        idx = torch.argsort(-r, axis=-1)[:, :C]
        idx_e = (lambda x, n, axis: torch.repeat_interleave(x, n, dim=axis))(idx.reshape(B, C, 1), D, axis=2)
        x_sel = (lambda x, i, axis: torch.take_along_dim(x, i, dim=axis))(x, idx_e, axis=1)
        g = _silu(x_sel @ w_gate)
        u = x_sel @ w_up
        y = g * u @ w_down
        r_sel = _sigmoid((lambda x, i, axis: torch.take_along_dim(x, i, dim=axis))(r, idx, axis=1))
        y = y * r_sel.reshape(B, C, 1)
        b_off = (torch.arange(B) * S).reshape(B, 1)
        flat_idx = (idx + b_off).reshape(B * C)
        zero = (x * 0.0).reshape(B * S, D)
        upd = _scatter_add(zero, flat_idx, y.reshape(B * C, D), axis=0)
        return x + upd.reshape(B, S, D)
    x = A_x
    xn = _layernorm(x, axis=-1)
    return x + _A_ref(xn, A_mem0, A_Wq, A_Wk, A_Wv, A_Wo, A_seg_len) + _B_ref(xn, B_w_r, B_w_gate, B_w_up, B_w_down)
```

```cpp
#include <cuda_runtime.h>
#include <cuda_bf16.h>
#include <cuda.h>
#include <stdint.h>

typedef __nv_bfloat16 bf16;

namespace {

constexpr int S_ = 2048, D_ = 1024, H_ = 32, DH_ = 128, HD_ = 4096, MT_ = 8, SEG_ = 32, NSEG_ = 64, F_ = 3584;

__device__ __align__(1024) bf16 g_xn[S_ * D_];
__device__ __align__(1024) bf16 g_q[S_ * HD_];
__device__ __align__(1024) bf16 g_k[S_ * HD_];
__device__ __align__(1024) bf16 g_v[S_ * HD_];
__device__ __align__(1024) bf16 g_o[S_ * HD_];
__device__ __align__(1024) float g_memacc[NSEG_ * MT_ * D_];
__device__ __align__(1024) unsigned g_cnt[NSEG_ * 3 * 32];
__device__ __align__(128) unsigned g_resident[32];
__device__ __align__(1024) unsigned g_prog[NSEG_ * 32];
__device__ __align__(1024) bf16 g_km[NSEG_ * MT_ * HD_];
__device__ __align__(1024) bf16 g_vm[NSEG_ * MT_ * HD_];
__device__ float g_r[S_];
__device__ float g_h[2 * F_];
__device__ float g_upd[2 * D_];
__device__ int g_idx[2];

#define TL_START(id)
#define TL_END(id)
__device__ __forceinline__ float bf16r(float x) { return __bfloat162float(__float2bfloat16_rn(x)); }
__device__ __forceinline__ uint32_t pack_bf16(float lo, float hi) {
    __nv_bfloat162 t = __floats2bfloat162_rn(lo, hi);
    return *reinterpret_cast<uint32_t*>(&t);
}
__device__ __forceinline__ float bf_lo(uint32_t u) { return __uint_as_float(u << 16); }
__device__ __forceinline__ float bf_hi(uint32_t u) { return __uint_as_float(u & 0xffff0000u); }
__device__ __forceinline__ uint32_t smem_u32(const void* p) { return (uint32_t)__cvta_generic_to_shared(p); }

__device__ __forceinline__ void mbar_init(uint32_t a, uint32_t cnt) {
    asm volatile("mbarrier.init.shared::cta.b64 [%0], %1;" ::"r"(a), "r"(cnt) : "memory");
}
__device__ __forceinline__ void mbar_expect_tx(uint32_t a, uint32_t bytes) {
    asm volatile("mbarrier.arrive.expect_tx.shared::cta.b64 _, [%0], %1;" ::"r"(a), "r"(bytes) : "memory");
}
__device__ __forceinline__ void mbar_wait(uint32_t a, uint32_t parity) {
    asm volatile(
        "{\n"
        ".reg .pred p;\n"
        "WAIT_%=:\n"
        "mbarrier.try_wait.parity.shared::cta.b64 p, [%0], %1;\n"
        "@p bra DONE_%=;\n"
        "bra WAIT_%=;\n"
        "DONE_%=:\n"
        "}\n" ::"r"(a), "r"(parity) : "memory");
}
__device__ __forceinline__ uint32_t mapa(uint32_t a, uint32_t rank) {
    uint32_t r;
    asm volatile("mapa.shared::cluster.u32 %0, %1, %2;" : "=r"(r) : "r"(a), "r"(rank));
    return r;
}
__device__ __forceinline__ void mbar_arrive_cluster(uint32_t remote_a) {
    asm volatile("mbarrier.arrive.shared::cluster.b64 _, [%0];" ::"r"(remote_a) : "memory");
}
__device__ __forceinline__ void cluster_arrive() { asm volatile("barrier.cluster.arrive.release.aligned;" ::: "memory"); }
__device__ __forceinline__ void cluster_wait() { asm volatile("barrier.cluster.wait.acquire.aligned;" ::: "memory"); }
__device__ __forceinline__ uint32_t cluster_ctarank() {
    uint32_t r;
    asm volatile("mov.u32 %0, %%cluster_ctarank;" : "=r"(r));
    return r;
}
__device__ __forceinline__ void tma_load_2d(uint32_t dst, const CUtensorMap* map, uint32_t bar, int c0, int c1) {
    asm volatile(
        "cp.async.bulk.tensor.2d.shared::cluster.global.mbarrier::complete_tx::bytes [%0], [%1, {%3, %4}], [%2];" ::"r"(dst),
        "l"(map), "r"(bar), "r"(c0), "r"(c1)
        : "memory");
}
__device__ __forceinline__ void tma_load_2d_mc(uint32_t dst, const CUtensorMap* map, uint32_t bar, int c0, int c1,
                                               uint16_t mask) {
    asm volatile(
        "cp.async.bulk.tensor.2d.shared::cluster.global.mbarrier::complete_tx::bytes.multicast::cluster [%0], [%1, {%3, "
        "%4}], [%2], %5;" ::"r"(dst),
        "l"(map), "r"(bar), "r"(c0), "r"(c1), "h"(mask)
        : "memory");
}
__device__ __forceinline__ void mma16816(float (&d)[4], uint32_t a0, uint32_t a1, uint32_t a2, uint32_t a3, uint32_t b0,
                                         uint32_t b1) {
    asm volatile(
        "mma.sync.aligned.m16n8k16.row.col.f32.bf16.bf16.f32 {%0,%1,%2,%3}, {%4,%5,%6,%7}, {%8,%9}, {%0,%1,%2,%3};"
        : "+f"(d[0]), "+f"(d[1]), "+f"(d[2]), "+f"(d[3])
        : "r"(a0), "r"(a1), "r"(a2), "r"(a3), "r"(b0), "r"(b1));
}
__device__ __forceinline__ void ldsm_x4(uint32_t& r0, uint32_t& r1, uint32_t& r2, uint32_t& r3, uint32_t a) {
    asm volatile("ldmatrix.sync.aligned.m8n8.x4.shared.b16 {%0,%1,%2,%3}, [%4];"
                 : "=r"(r0), "=r"(r1), "=r"(r2), "=r"(r3)
                 : "r"(a)
                 : "memory");
}
__device__ __forceinline__ void ldsm_x4_t(uint32_t& r0, uint32_t& r1, uint32_t& r2, uint32_t& r3, uint32_t a) {
    asm volatile("ldmatrix.sync.aligned.m8n8.x4.trans.shared.b16 {%0,%1,%2,%3}, [%4];"
                 : "=r"(r0), "=r"(r1), "=r"(r2), "=r"(r3)
                 : "r"(a)
                 : "memory");
}
__device__ __forceinline__ void ldsm_x2_t(uint32_t& r0, uint32_t& r1, uint32_t a) {
    asm volatile("ldmatrix.sync.aligned.m8n8.x2.trans.shared.b16 {%0,%1}, [%2];" : "=r"(r0), "=r"(r1) : "r"(a) : "memory");
}
__device__ __forceinline__ uint32_t movm_t(uint32_t a) {
    uint32_t d;
    asm volatile("movmatrix.sync.aligned.m8n8.trans.b16 %0, %1;" : "=r"(d) : "r"(a));
    return d;
}
__device__ __forceinline__ void cp_async16(uint32_t dst, const void* src) {
    asm volatile("cp.async.cg.shared.global [%0], [%1], 16;" ::"r"(dst), "l"(src) : "memory");
}
__device__ __forceinline__ void cp_async_commit() { asm volatile("cp.async.commit_group;" ::: "memory"); }
__device__ __forceinline__ void cp_async_wait_all() { asm volatile("cp.async.wait_all;" ::: "memory"); }

__global__ void __launch_bounds__(256) ln_kernel(const bf16* __restrict__ x, const bf16* __restrict__ w_r,
                                                 const bf16* __restrict__ mem0) {
    const int warp = threadIdx.x >> 5, lane = threadIdx.x & 31;
    TL_START(0);
    const int row = blockIdx.x * 8 + warp;
    const uint4* xp = reinterpret_cast<const uint4*>(x + (size_t)row * D_);
    const uint4* wp = reinterpret_cast<const uint4*>(w_r);
    float v[32];
    float sum = 0.f;
#pragma unroll
    for (int c = 0; c < 4; c++) {
        uint4 u = xp[c * 32 + lane];
        uint32_t w[4] = {u.x, u.y, u.z, u.w};
#pragma unroll
        for (int i = 0; i < 4; i++) {
            v[c * 8 + 2 * i] = bf_lo(w[i]);
            v[c * 8 + 2 * i + 1] = bf_hi(w[i]);
            sum += v[c * 8 + 2 * i] + v[c * 8 + 2 * i + 1];
        }
    }
#pragma unroll
    for (int o = 16; o; o >>= 1) sum += __shfl_xor_sync(0xffffffffu, sum, o);
    const float mean = sum * (1.0f / D_);
    float sq = 0.f;
#pragma unroll
    for (int i = 0; i < 32; i++) {
        float d = v[i] - mean;
        sq += d * d;
    }
#pragma unroll
    for (int o = 16; o; o >>= 1) sq += __shfl_xor_sync(0xffffffffu, sq, o);
    const float mb = bf16r(mean);
    const float vb = bf16r(sq * (1.0f / D_));
    const float den = bf16r(sqrtf(bf16r(vb + 1e-5f)));
    float racc = 0.f;
    uint4* op = reinterpret_cast<uint4*>(g_xn + (size_t)row * D_);
#pragma unroll
    for (int c = 0; c < 4; c++) {
        uint4 wu = wp[c * 32 + lane];
        uint32_t ww[4] = {wu.x, wu.y, wu.z, wu.w};
        uint32_t o[4];
#pragma unroll
        for (int i = 0; i < 4; i++) {
            float a = bf16r(__fdiv_rn(bf16r(v[c * 8 + 2 * i] - mb), den));
            float b = bf16r(__fdiv_rn(bf16r(v[c * 8 + 2 * i + 1] - mb), den));
            racc += a * bf_lo(ww[i]) + b * bf_hi(ww[i]);
            o[i] = pack_bf16(a, b);
        }
        op[c * 32 + lane] = make_uint4(o[0], o[1], o[2], o[3]);
    }
#pragma unroll
    for (int o = 16; o; o >>= 1) racc += __shfl_xor_sync(0xffffffffu, racc, o);
    if (lane == 0) g_r[row] = bf16r(racc);

    {
        const int per = NSEG_ * MT_ * D_ / 256;
        float4* mp = reinterpret_cast<float4*>(g_memacc + (size_t)blockIdx.x * per);
        for (int i = threadIdx.x; i < per / 4; i += 256) {
            int e = blockIdx.x * per + i * 4;
            float4 z = make_float4(0.f, 0.f, 0.f, 0.f);
            if (e < MT_ * D_) {
                z.x = __bfloat162float(mem0[e]);
                z.y = __bfloat162float(mem0[e + 1]);
                z.z = __bfloat162float(mem0[e + 2]);
                z.w = __bfloat162float(mem0[e + 3]);
            }
            mp[i] = z;
        }
        if (threadIdx.x < NSEG_ * 3 * 32 / 256) g_cnt[blockIdx.x * (NSEG_ * 3 * 32 / 256) + threadIdx.x] = 0u;
        if (threadIdx.x < NSEG_ * 32 / 256) g_prog[blockIdx.x * (NSEG_ * 32 / 256) + threadIdx.x] = 0u;
        if (blockIdx.x == 0 && threadIdx.x == 0) g_resident[0] = 0u;
    }
    TL_END(0);
}

__device__ __forceinline__ void top2_block(int& i0, int& i1, float* sv, int* si) {
    const int tid = threadIdx.x;
    float b0 = -INFINITY, b1 = -INFINITY;
    int j0 = 0x7fffffff, j1 = 0x7fffffff;
    for (int t = tid; t < S_; t += 256) {
        float v = g_r[t];
        if (v > b0 || (v == b0 && t < j0)) {
            b1 = b0; j1 = j0; b0 = v; j0 = t;
        } else if (v > b1 || (v == b1 && t < j1)) {
            b1 = v; j1 = t;
        }
    }
    sv[tid * 2] = b0; si[tid * 2] = j0; sv[tid * 2 + 1] = b1; si[tid * 2 + 1] = j1;
    __syncthreads();
    if (tid < 32) {
        float c0 = -INFINITY, c1 = -INFINITY;
        int k0 = 0x7fffffff, k1 = 0x7fffffff;
        for (int t = tid; t < 512; t += 32) {
            float v = sv[t]; int id = si[t];
            if (v > c0 || (v == c0 && id < k0)) {
                c1 = c0; k1 = k0; c0 = v; k0 = id;
            } else if (v > c1 || (v == c1 && id < k1)) {
                c1 = v; k1 = id;
            }
        }
#pragma unroll
        for (int o = 16; o; o >>= 1) {
            float d0 = __shfl_xor_sync(0xffffffffu, c0, o), d1 = __shfl_xor_sync(0xffffffffu, c1, o);
            int e0 = __shfl_xor_sync(0xffffffffu, k0, o), e1 = __shfl_xor_sync(0xffffffffu, k1, o);
            bool dfirst = (d0 > c0) || (d0 == c0 && e0 < k0);
            float n0 = dfirst ? d0 : c0; int m0 = dfirst ? e0 : k0;
            float a = dfirst ? c0 : d0; int ai = dfirst ? k0 : e0;
            float b = dfirst ? d1 : c1; int bi = dfirst ? e1 : k1;
            bool afirst = (a > b) || (a == b && ai < bi);
            c0 = n0; k0 = m0; c1 = afirst ? a : b; k1 = afirst ? ai : bi;
        }
        if (tid == 0) { si[0] = k0; si[1] = k1; }
    }
    __syncthreads();
    i0 = si[0]; i1 = si[1];
    __syncthreads();
}

__global__ void __launch_bounds__(256) ffn1_kernel(const bf16* __restrict__ wg, const bf16* __restrict__ wu) {
    __shared__ float sv[512];
    __shared__ int si[512];
    __shared__ float sx[2][D_];
    __shared__ float red[64][4][33];
    int i0, i1;
    TL_START(1);
    top2_block(i0, i1, sv, si);
    const int tid = threadIdx.x;
    if (blockIdx.x == 0 && tid == 0) { g_idx[0] = i0; g_idx[1] = i1; }
    for (int t = tid; t < D_; t += 256) {
        sx[0][t] = __bfloat162float(g_xn[(size_t)i0 * D_ + t]);
        sx[1][t] = __bfloat162float(g_xn[(size_t)i1 * D_ + t]);
    }
    __syncthreads();
    const int cq = tid & 3, rg = tid >> 2;
    const int col0 = blockIdx.x * 32 + cq * 8;
    float acc[4][8];
#pragma unroll
    for (int a = 0; a < 4; a++)
#pragma unroll
        for (int b = 0; b < 8; b++) acc[a][b] = 0.f;
#pragma unroll 4
    for (int p = 0; p < 16; p++) {
        int d = p * 64 + rg;
        uint4 ug = __ldg(reinterpret_cast<const uint4*>(wg + (size_t)d * F_ + col0));
        uint4 uu = __ldg(reinterpret_cast<const uint4*>(wu + (size_t)d * F_ + col0));
        float x0 = sx[0][d], x1 = sx[1][d];
        uint32_t a[4] = {ug.x, ug.y, ug.z, ug.w}, b[4] = {uu.x, uu.y, uu.z, uu.w};
#pragma unroll
        for (int i = 0; i < 4; i++) {
            acc[0][2 * i] += x0 * bf_lo(a[i]); acc[0][2 * i + 1] += x0 * bf_hi(a[i]);
            acc[1][2 * i] += x1 * bf_lo(a[i]); acc[1][2 * i + 1] += x1 * bf_hi(a[i]);
            acc[2][2 * i] += x0 * bf_lo(b[i]); acc[2][2 * i + 1] += x0 * bf_hi(b[i]);
            acc[3][2 * i] += x1 * bf_lo(b[i]); acc[3][2 * i + 1] += x1 * bf_hi(b[i]);
        }
    }
#pragma unroll
    for (int a = 0; a < 4; a++)
#pragma unroll
        for (int b = 0; b < 8; b++) red[rg][a][cq * 8 + b] = acc[a][b];
    __syncthreads();
    if (tid < 128) {
        int a = tid >> 5, c = tid & 31;
        float s = 0.f;
        for (int r = 0; r < 64; r++) s += red[r][a][c];
        red[0][a][c] = bf16r(s);
    }
    __syncthreads();
    if (tid < 64) {
        int tk = tid >> 5, c = tid & 31;
        float g = red[0][tk][c], u = red[0][2 + tk][c];
        float sg = bf16r(g / (1.0f + __expf(-g)));
        g_h[tk * F_ + blockIdx.x * 32 + c] = bf16r(sg * u);
    }
    TL_END(1);
}

__global__ void __launch_bounds__(256) ffn2_kernel(const bf16* __restrict__ wd) {
    __shared__ float sh[2][F_];
    __shared__ float red[128][2][17];
    const int tid = threadIdx.x;
    TL_START(2);
    for (int t = tid; t < 2 * F_; t += 256) (&sh[0][0])[t] = g_h[t];
    __syncthreads();
    const int ch = tid & 1, rg = tid >> 1;
    const int col0 = blockIdx.x * 16 + ch * 8;
    float acc[2][8];
#pragma unroll
    for (int b = 0; b < 8; b++) acc[0][b] = acc[1][b] = 0.f;
#pragma unroll 7
    for (int p = 0; p < 28; p++) {
        int f = p * 128 + rg;
        uint4 u = __ldg(reinterpret_cast<const uint4*>(wd + (size_t)f * D_ + col0));
        float h0 = sh[0][f], h1 = sh[1][f];
        uint32_t a[4] = {u.x, u.y, u.z, u.w};
#pragma unroll
        for (int i = 0; i < 4; i++) {
            acc[0][2 * i] += h0 * bf_lo(a[i]); acc[0][2 * i + 1] += h0 * bf_hi(a[i]);
            acc[1][2 * i] += h1 * bf_lo(a[i]); acc[1][2 * i + 1] += h1 * bf_hi(a[i]);
        }
    }
#pragma unroll
    for (int b = 0; b < 8; b++) { red[rg][0][ch * 8 + b] = acc[0][b]; red[rg][1][ch * 8 + b] = acc[1][b]; }
    __syncthreads();
    if (tid < 32) {
        int tk = tid >> 4, c = tid & 15;
        float s = 0.f;
        for (int r = 0; r < 128; r++) s += red[r][tk][c];
        float y = bf16r(s);
        float rv = g_r[g_idx[tk]];
        float sg = bf16r(1.0f / (1.0f + __expf(-rv)));
        g_upd[tk * D_ + blockIdx.x * 16 + c] = bf16r(y * sg);
    }
    TL_END(2);
}

__device__ __forceinline__ uint64_t make_desc(uint32_t addr, uint32_t lbo_bytes, uint32_t sbo_bytes) {
    return (uint64_t)((addr & 0x3FFFF) >> 4) | ((uint64_t)(lbo_bytes >> 4) << 16) | ((uint64_t)(sbo_bytes >> 4) << 32) |
           (1ull << 62);
}
__device__ __forceinline__ void wgmma_fence() { asm volatile("wgmma.fence.sync.aligned;" ::: "memory"); }
__device__ __forceinline__ void wgmma_commit() { asm volatile("wgmma.commit_group.sync.aligned;" ::: "memory"); }
template <int N>
__device__ __forceinline__ void wgmma_wait() { asm volatile("wgmma.wait_group.sync.aligned %0;" ::"n"(N) : "memory"); }

#define ACC8(b) "+f"(d[b]), "+f"(d[b + 1]), "+f"(d[b + 2]), "+f"(d[b + 3]), "+f"(d[b + 4]), "+f"(d[b + 5]), "+f"(d[b + 6]), "+f"(d[b + 7])
#define ACC32(b) ACC8(b), ACC8(b + 8), ACC8(b + 16), ACC8(b + 24)

__device__ __forceinline__ void wgmma_n128(float (&d)[64], uint64_t da, uint64_t db, int scale_d) {
    asm volatile(
        "{\n.reg .pred p;\nsetp.ne.b32 p, %66, 0;\n"
        "wgmma.mma_async.sync.aligned.m64n128k16.f32.bf16.bf16 "
        "{%0,%1,%2,%3,%4,%5,%6,%7,%8,%9,%10,%11,%12,%13,%14,%15,%16,%17,%18,%19,%20,%21,%22,%23,%24,%25,%26,%27,%28,%29,%30,%31,"
        "%32,%33,%34,%35,%36,%37,%38,%39,%40,%41,%42,%43,%44,%45,%46,%47,%48,%49,%50,%51,%52,%53,%54,%55,%56,%57,%58,%59,%60,%61,%62,%63},"
        " %64, %65, p, 1, 1, 0, 1;\n}\n"
        : ACC32(0), ACC32(32)
        : "l"(da), "l"(db), "r"(scale_d));
}
__device__ __forceinline__ void wgmma_n256(float (&d)[128], uint64_t da, uint64_t db, int scale_d) {
    asm volatile(
        "{\n.reg .pred p;\nsetp.ne.b32 p, %130, 0;\n"
        "wgmma.mma_async.sync.aligned.m64n256k16.f32.bf16.bf16 "
        "{%0,%1,%2,%3,%4,%5,%6,%7,%8,%9,%10,%11,%12,%13,%14,%15,%16,%17,%18,%19,%20,%21,%22,%23,%24,%25,%26,%27,%28,%29,%30,%31,"
        "%32,%33,%34,%35,%36,%37,%38,%39,%40,%41,%42,%43,%44,%45,%46,%47,%48,%49,%50,%51,%52,%53,%54,%55,%56,%57,%58,%59,%60,%61,%62,%63,"
        "%64,%65,%66,%67,%68,%69,%70,%71,%72,%73,%74,%75,%76,%77,%78,%79,%80,%81,%82,%83,%84,%85,%86,%87,%88,%89,%90,%91,%92,%93,%94,%95,"
        "%96,%97,%98,%99,%100,%101,%102,%103,%104,%105,%106,%107,%108,%109,%110,%111,%112,%113,%114,%115,%116,%117,%118,%119,%120,%121,%122,%123,%124,%125,%126,%127},"
        " %128, %129, p, 1, 1, 0, 1;\n}\n"
        : ACC32(0), ACC32(32), ACC32(64), ACC32(96)
        : "l"(da), "l"(db), "r"(scale_d));
}

template <int BN, int STAGES>
struct GemmSmem {
    static constexpr int A_BYTES = 128 * 64 * 2;
    static constexpr int B_BYTES = BN * 64 * 2;
    static constexpr int STAGE_BYTES = A_BYTES + B_BYTES;
    static constexpr int TOTAL = STAGES * STAGE_BYTES + 1024   + 256  ;
};

template <int BN, int STAGES, int KT, int EPI>
__global__ void __launch_bounds__(384, 1)
    gemm_kernel(const __grid_constant__ CUtensorMap tmA, const __grid_constant__ CUtensorMap tmB0,
                const __grid_constant__ CUtensorMap tmB1, const __grid_constant__ CUtensorMap tmB2,
                const bf16* __restrict__ xin, bf16* __restrict__ out, int n_tile_base, int m_tile_base) {
    using L = GemmSmem<BN, STAGES>;
    extern __shared__ uint8_t smem_raw[];
    const uint32_t sbase = (smem_u32(smem_raw) + 1023u) & ~1023u;
    const uint32_t bar_base = sbase + STAGES * L::STAGE_BYTES;
    auto full_bar = [&](int s) { return bar_base + s * 8; };
    auto empty_bar = [&](int s) { return bar_base + 64 + s * 8; };
    const int tid = threadIdx.x, wg = tid >> 7;
    const int m0 = (blockIdx.x + m_tile_base) * 128;
    const int ntile = blockIdx.y + n_tile_base;
    TL_START(EPI == 0 ? (n_tile_base ? 3 : 4) : 30 + m_tile_base);

    if (tid == 0) {
        for (int s = 0; s < STAGES; s++) {
            mbar_init(full_bar(s), 1);
            mbar_init(empty_bar(s), 2);
        }
        asm volatile("fence.mbarrier_init.release.cluster;" ::: "memory");
    }
    __syncthreads();

    if (wg == 0) {
        asm volatile("setmaxnreg.dec.sync.aligned.u32 40;");
        if (tid == 0) {
            const CUtensorMap* tb;
            int n0;
            if (EPI == 0) {
                const int which = ntile / (HD_ / BN);
                tb = which == 0 ? &tmB0 : (which == 1 ? &tmB1 : &tmB2);
                n0 = (ntile % (HD_ / BN)) * BN;
            } else {
                tb = &tmB0;
                n0 = ntile * BN;
            }
            for (int kt = 0; kt < KT; kt++) {
                const int s = kt % STAGES;
                const uint32_t ph = (kt / STAGES) & 1;
                mbar_wait(empty_bar(s), ph ^ 1);
                mbar_expect_tx(full_bar(s), L::STAGE_BYTES);
                const uint32_t sa = sbase + s * L::STAGE_BYTES;
                tma_load_2d(sa, &tmA, full_bar(s), kt * 64, m0);
#pragma unroll
                for (int box = 0; box < BN / 64; box++)
                    tma_load_2d(sa + L::A_BYTES + box * 8192, tb, full_bar(s), n0 + box * 64, kt * 64);
            }
        }
    } else {
        asm volatile("setmaxnreg.inc.sync.aligned.u32 232;");
        const int cw = wg - 1;
        float acc[BN / 2];
        for (int kt = 0; kt < KT; kt++) {
            const int s = kt % STAGES;
            const uint32_t ph = (kt / STAGES) & 1;
            mbar_wait(full_bar(s), ph);
            const uint32_t sa = sbase + s * L::STAGE_BYTES + cw * 8192;
            const uint32_t sb = sbase + s * L::STAGE_BYTES + L::A_BYTES;
            wgmma_fence();
#pragma unroll
            for (int kk = 0; kk < 4; kk++) {
                uint64_t da = make_desc(sa + kk * 32, 16, 1024);
                uint64_t db = make_desc(sb + kk * 2048, 8192, 1024);
                if constexpr (BN == 256) wgmma_n256(acc, da, db, (kt | kk) != 0);
                else wgmma_n128(acc, da, db, (kt | kk) != 0);
            }
            wgmma_commit();
            if (kt > 0) {
                wgmma_wait<1>();
                if ((tid & 127) == 0) {
                    const int ps = (kt - 1) % STAGES;
                    asm volatile("mbarrier.arrive.shared::cta.b64 _, [%0];" ::"r"(empty_bar(ps)) : "memory");
                }
            }
        }
        wgmma_wait<0>();
        asm volatile("bar.sync 1, 256;" ::: "memory");
        constexpr int ROWB = BN * 2 + 16;
        const uint32_t stg = sbase + cw * (64 * ROWB);
        const int wq = (tid >> 5) & 3, lane = tid & 31, g = lane >> 2, j = lane & 3;
#pragma unroll
        for (int c = 0; c < BN / 8; c++) {
            uint32_t lo = pack_bf16(acc[c * 4], acc[c * 4 + 1]);
            uint32_t hi = pack_bf16(acc[c * 4 + 2], acc[c * 4 + 3]);
            uint32_t a0 = stg + (wq * 16 + g) * ROWB + c * 16 + j * 4;
            asm volatile("st.shared.b32 [%0], %1;" ::"r"(a0), "r"(lo) : "memory");
            asm volatile("st.shared.b32 [%0], %1;" ::"r"(a0 + 8 * ROWB), "r"(hi) : "memory");
        }
        __syncwarp();
        constexpr int CPR = BN / 8;
        if (EPI == 0) {
            const int which = ntile / (HD_ / BN);
            bf16* dst = which == 0 ? g_q : (which == 1 ? g_k : g_v);
            const int n0 = (ntile % (HD_ / BN)) * BN;
#pragma unroll
            for (int it = 0; it < 16 * CPR / 32; it++) {
                int idx = it * 32 + lane;
                int r = idx / CPR, ch = idx % CPR;
                uint4 v;
                asm volatile("ld.shared.v4.b32 {%0,%1,%2,%3}, [%4];"
                             : "=r"(v.x), "=r"(v.y), "=r"(v.z), "=r"(v.w)
                             : "r"(stg + (wq * 16 + r) * ROWB + ch * 16));
                int row = m0 + cw * 64 + wq * 16 + r;
                *reinterpret_cast<uint4*>(dst + (size_t)row * HD_ + n0 + ch * 8) = v;
            }
        } else {
            const int n0 = ntile * BN;
            const int i0 = g_idx[0], i1 = g_idx[1];
#pragma unroll
            for (int it = 0; it < 16 * CPR / 32; it++) {
                int idx = it * 32 + lane;
                int r = idx / CPR, ch = idx % CPR;
                uint4 v;
                asm volatile("ld.shared.v4.b32 {%0,%1,%2,%3}, [%4];"
                             : "=r"(v.x), "=r"(v.y), "=r"(v.z), "=r"(v.w)
                             : "r"(stg + (wq * 16 + r) * ROWB + ch * 16));
                int row = m0 + cw * 64 + wq * 16 + r;
                size_t off = (size_t)row * D_ + n0 + ch * 8;
                uint4 xv = __ldg(reinterpret_cast<const uint4*>(xin + off));
                uint4 nv = *reinterpret_cast<const uint4*>(g_xn + off);
                uint32_t av[4] = {v.x, v.y, v.z, v.w}, xa[4] = {xv.x, xv.y, xv.z, xv.w}, na[4] = {nv.x, nv.y, nv.z, nv.w};
                uint32_t ov[4];
                const float* up = (row == i0) ? (g_upd + n0 + ch * 8) : ((row == i1) ? (g_upd + D_ + n0 + ch * 8) : nullptr);
#pragma unroll
                for (int i = 0; i < 4; i++) {
                    float b0 = bf_lo(na[i]), b1 = bf_hi(na[i]);
                    if (up) { b0 = bf16r(b0 + up[2 * i]); b1 = bf16r(b1 + up[2 * i + 1]); }
                    float t0 = bf16r(bf_lo(xa[i]) + bf_lo(av[i])), t1 = bf16r(bf_hi(xa[i]) + bf_hi(av[i]));
                    ov[i] = pack_bf16(t0 + b0, t1 + b1);
                }
                *reinterpret_cast<uint4*>(out + off) = make_uint4(ov[0], ov[1], ov[2], ov[3]);
            }
        }
    }
}

constexpr int NRF = 44;
constexpr int RB = 272;
constexpr int SM_WSM = 0;
constexpr int SM_WO = SM_WSM + (64 - NRF) * 8 * 512;
constexpr int SM_PART = SM_WO + 22 * 8 * 512;
constexpr int SM_Q = SM_PART + 8 * 8 * 132 * 4;
constexpr int SM_K = SM_Q + 8 * RB;
constexpr int SM_V = SM_K + 40 * RB;
constexpr int SM_XBAR = SM_V + 48 * RB;
constexpr int SM_TOTAL = SM_XBAR + 16;
constexpr int SM_O = SM_PART;
constexpr int SM_S = SM_PART + 8 * RB;

#define PROF(i)
__device__ __forceinline__ float4 ld_poll4(const float4* p) {
    float4 v;
    asm volatile("ld.relaxed.gpu.global.v4.f32 {%0,%1,%2,%3}, [%4];" : "=f"(v.x), "=f"(v.y), "=f"(v.z), "=f"(v.w) : "l"(p) : "memory");
    return v;
}
__device__ __forceinline__ unsigned ld_acquire(const unsigned* p) {
    unsigned v;
    asm volatile("ld.acquire.gpu.global.u32 %0, [%1];" : "=r"(v) : "l"(p) : "memory");
    return v;
}

__global__ void __cluster_dims__(3, 1, 1) __launch_bounds__(256, 1)
    rec_kernel(const bf16* __restrict__ Wq, const bf16* __restrict__ Wk, const bf16* __restrict__ Wv,
               const bf16* __restrict__ Wo) {
    extern __shared__ __align__(1024) uint8_t smem[];
    const uint32_t sb = smem_u32(smem);
    const int tid = threadIdx.x, w = tid >> 5, lane = tid & 31, g = lane >> 2, j = lane & 3;
    const uint32_t rank = cluster_ctarank();
    const int h = blockIdx.x / 3;
    const bf16* W = rank == 0 ? Wq : (rank == 1 ? Wk : Wv);
    const int tile0 = rank == 0 ? 0 : (rank == 1 ? 22 : 43);
    const int ntiles = rank == 0 ? 22 : 21;

    TL_START(5);
    if (threadIdx.x == 0) atomicAdd(&g_resident[0], 1u);
    auto prefetch_kv = [&](int s) {
#pragma unroll
        for (int it = 0; it < 2; it++) {
            int idx = it * 256 + tid;
            int r = idx >> 4, ch = idx & 15;
            size_t off = (size_t)(s * SEG_ + r) * HD_ + h * DH_ + ch * 8;
            cp_async16(sb + SM_K + (8 + r) * RB + ch * 16, g_k + off);
            cp_async16(sb + SM_V + (8 + r) * RB + ch * 16, g_v + off);
        }
        cp_async_commit();
    };
    prefetch_kv(0);
    for (int i = tid; i < 8 * RB / 4; i += 256) *reinterpret_cast<uint32_t*>(smem + SM_V + 40 * RB + i * 4) = 0u;

    uint32_t wreg[NRF][4];
    {
        const int klo = 4 * (g >> 1) + (g & 1);
        const bf16* wbase = W + (size_t)(128 * w) * HD_ + h * DH_ + 2 * j;
#pragma unroll
        for (int f = 0; f < 64; f++) {
            const int i = f >> 3, mt = f & 7;
            const bf16* p = wbase + (size_t)(16 * i + klo) * HD_ + 16 * mt;
            uint32_t r0 = __ldg(reinterpret_cast<const uint32_t*>(p));
            uint32_t r1 = __ldg(reinterpret_cast<const uint32_t*>(p + 8));
            uint32_t r2 = __ldg(reinterpret_cast<const uint32_t*>(p + 2 * HD_));
            uint32_t r3 = __ldg(reinterpret_cast<const uint32_t*>(p + 2 * HD_ + 8));
            r0 = movm_t(r0); r1 = movm_t(r1); r2 = movm_t(r2); r3 = movm_t(r3);
            if (f < NRF) {
                wreg[f < NRF ? f : 0][0] = r0; wreg[f < NRF ? f : 0][1] = r1;
                wreg[f < NRF ? f : 0][2] = r2; wreg[f < NRF ? f : 0][3] = r3;
            } else {
                *reinterpret_cast<uint4*>(smem + SM_WSM + ((f - NRF) * 8 + w) * 512 + lane * 16) = make_uint4(r0, r1, r2, r3);
            }
        }
        for (int t = w; t < ntiles; t += 8) {
#pragma unroll
            for (int i = 0; i < 8; i++) {
                const bf16* p = Wo + (size_t)(h * DH_ + 16 * i + g) * D_ + (tile0 + t) * 16 + 4 * j;
                uint32_t r0 = __ldg(reinterpret_cast<const uint32_t*>(p));
                uint32_t r1 = __ldg(reinterpret_cast<const uint32_t*>(p + 2));
                uint32_t r2 = __ldg(reinterpret_cast<const uint32_t*>(p + 8 * D_));
                uint32_t r3 = __ldg(reinterpret_cast<const uint32_t*>(p + 8 * D_ + 2));
                r0 = movm_t(r0); r1 = movm_t(r1); r2 = movm_t(r2); r3 = movm_t(r3);
                *reinterpret_cast<uint4*>(smem + SM_WO + (t * 8 + i) * 512 + lane * 16) = make_uint4(r0, r1, r2, r3);
            }
        }
    }
    if (tid == 0) {
        mbar_init(sb + SM_XBAR, 1);
        asm volatile("fence.mbarrier_init.release.cluster;" ::: "memory");
    }
    __syncthreads();
    cluster_arrive();
    cluster_wait();

    const uint32_t dst_local = sb + (rank == 0 ? SM_Q : (rank == 1 ? SM_K : SM_V)) + w * RB + lane * 8;
    const uint32_t dst0 = mapa(dst_local, 0), dst1 = mapa(dst_local, 1), dst2 = mapa(dst_local, 2);
    const uint32_t xb0 = mapa(sb + SM_XBAR, 0), xb1 = mapa(sb + SM_XBAR, 1), xb2 = mapa(sb + SM_XBAR, 2);
    const bool three = w + 16 < ntiles;
    const int ra = w <= 2 ? 0 : (w <= 5 ? 1 : 2);
    const int rb2 = (w == 2) ? 1 : ((w == 5) ? 2 : ra);
    const float scale = 0.08838834764831845f;

    for (int s = 0; s < NSEG_; s++) {
        PROF(0);
        if (tid == 0) mbar_expect_tx(sb + SM_XBAR, 3 * 2048);
        if (s > 0) {
            if (lane < 2) {
                const unsigned* cp = g_cnt + (s * 3 + (lane == 0 ? ra : rb2)) * 32;
                int guard = 0;
                while (ld_acquire(cp) < 32u && ++guard < (1 << 22)) {}
            }
            __syncwarp();
        }
        PROF(12);
        uint32_t bf[16];
        {
            const float4* mp = reinterpret_cast<const float4*>(g_memacc + (size_t)s * MT_ * D_ + g * D_ + 128 * w + 4 * j);
            float4 mv[8];
#pragma unroll
            for (int i = 0; i < 8; i++) mv[i] = ld_poll4(mp + 4 * i);
#pragma unroll
            for (int i = 0; i < 8; i++) {
                bf[2 * i] = pack_bf16(mv[i].x, mv[i].y);
                bf[2 * i + 1] = pack_bf16(mv[i].z, mv[i].w);
            }
        }
        PROF(1);
        float acc[8][4];
#pragma unroll
        for (int mt = 0; mt < 8; mt++) acc[mt][0] = acc[mt][1] = acc[mt][2] = acc[mt][3] = 0.f;
#pragma unroll
        for (int i = 0; i < 8; i++) {
            const uint32_t b0 = bf[2 * i], b1 = bf[2 * i + 1];
#pragma unroll
            for (int mt = 0; mt < 8; mt++) {
                const int f = i * 8 + mt;
                if (f < NRF) {
                    mma16816(acc[mt], wreg[f < NRF ? f : 0][0], wreg[f < NRF ? f : 0][1], wreg[f < NRF ? f : 0][2],
                             wreg[f < NRF ? f : 0][3], b0, b1);
                } else {
                    uint4 a = *reinterpret_cast<const uint4*>(smem + SM_WSM + ((f - NRF) * 8 + w) * 512 + lane * 16);
                    mma16816(acc[mt], a.x, a.y, a.z, a.w, b0, b1);
                }
            }
        }
        {
            float* pp = reinterpret_cast<float*>(smem + SM_PART) + w * (8 * 132);
#pragma unroll
            for (int mt = 0; mt < 8; mt++) {
                pp[(2 * j) * 132 + 16 * mt + g] = acc[mt][0];
                pp[(2 * j + 1) * 132 + 16 * mt + g] = acc[mt][1];
                pp[(2 * j) * 132 + 16 * mt + g + 8] = acc[mt][2];
                pp[(2 * j + 1) * 132 + 16 * mt + g + 8] = acc[mt][3];
            }
        }
        PROF(2);
        cp_async_wait_all();
        __syncthreads();
        PROF(3);
        {
            const float* pp = reinterpret_cast<const float*>(smem + SM_PART) + w * 132 + 4 * lane;
            float4 t = *reinterpret_cast<const float4*>(pp);
#pragma unroll
            for (int q = 1; q < 8; q++) {
                float4 u = *reinterpret_cast<const float4*>(pp + q * (8 * 132));
                t.x += u.x; t.y += u.y; t.z += u.z; t.w += u.w;
            }
            const uint32_t lo = pack_bf16(t.x, t.y), hi = pack_bf16(t.z, t.w);
            asm volatile("st.async.weak.shared::cluster.mbarrier::complete_tx::bytes.v2.b32 [%0], {%1,%2}, [%3];" ::"r"(dst0), "r"(lo), "r"(hi), "r"(xb0) : "memory");
            asm volatile("st.async.weak.shared::cluster.mbarrier::complete_tx::bytes.v2.b32 [%0], {%1,%2}, [%3];" ::"r"(dst1), "r"(lo), "r"(hi), "r"(xb1) : "memory");
            asm volatile("st.async.weak.shared::cluster.mbarrier::complete_tx::bytes.v2.b32 [%0], {%1,%2}, [%3];" ::"r"(dst2), "r"(lo), "r"(hi), "r"(xb2) : "memory");
            if (rank != 0) {
                bf16* gp = (rank == 1 ? g_km : g_vm) + (size_t)(s * MT_ + w) * HD_ + h * DH_ + 4 * lane;
                *reinterpret_cast<uint2*>(gp) = make_uint2(lo, hi);
            }
        }
        PROF(4);
        mbar_wait(sb + SM_XBAR, s & 1);
        PROF(5);
        if (s == NSEG_ - 1) break;
        if (w < 5) {
            float c0[4] = {0.f, 0.f, 0.f, 0.f}, c1[4] = {0.f, 0.f, 0.f, 0.f};
            const uint32_t qa = sb + SM_Q + (lane & 7) * RB + (lane >> 3) * 16;
            const uint32_t ka = sb + SM_K + (8 * w + (lane & 7)) * RB + (lane >> 3) * 16;
#pragma unroll
            for (int i2 = 0; i2 < 4; i2++) {
                uint32_t a0, a2, a0n, a2n, b0, b1, b0n, b1n;
                ldsm_x4(a0, a2, a0n, a2n, qa + i2 * 64);
                ldsm_x4(b0, b1, b0n, b1n, ka + i2 * 64);
                mma16816(c0, a0, 0u, a2, 0u, b0, b1);
                mma16816(c1, a0n, 0u, a2n, 0u, b0n, b1n);
            }
            float s0 = bf16r(bf16r(c0[0] + c1[0]) * scale), s1 = bf16r(bf16r(c0[1] + c1[1]) * scale);
            *reinterpret_cast<float2*>(smem + SM_S + (g * 40 + 8 * w + 2 * j) * 4) = make_float2(s0, s1);
        }
        __syncthreads();
        PROF(6);
        {
            const uint32_t va = sb + SM_V + (lane & 15) * RB + (16 * w + (lane >> 4) * 8) * 2;
            uint32_t vb[3][4];
#pragma unroll
            for (int i = 0; i < 3; i++) ldsm_x4_t(vb[i][0], vb[i][1], vb[i][2], vb[i][3], va + i * 16 * RB);
            float sv[5][2];
            float mx = -INFINITY;
#pragma unroll
            for (int t = 0; t < 5; t++) {
                float2 u = *reinterpret_cast<const float2*>(smem + SM_S + (g * 40 + 8 * t + 2 * j) * 4);
                sv[t][0] = u.x; sv[t][1] = u.y;
                mx = fmaxf(mx, fmaxf(u.x, u.y));
            }
            mx = fmaxf(mx, __shfl_xor_sync(0xffffffffu, mx, 1));
            mx = fmaxf(mx, __shfl_xor_sync(0xffffffffu, mx, 2));
            float sum = 0.f;
#pragma unroll
            for (int t = 0; t < 5; t++) {
                sv[t][0] = __expf(sv[t][0] - mx); sv[t][1] = __expf(sv[t][1] - mx);
                sum += sv[t][0] + sv[t][1];
            }
            sum += __shfl_xor_sync(0xffffffffu, sum, 1);
            sum += __shfl_xor_sync(0xffffffffu, sum, 2);
            const float inv = __frcp_rn(sum);
            uint32_t p[5];
#pragma unroll
            for (int t = 0; t < 5; t++) p[t] = pack_bf16(sv[t][0] * inv, sv[t][1] * inv);
            float o0[4] = {0.f, 0.f, 0.f, 0.f}, o1[4] = {0.f, 0.f, 0.f, 0.f};
            float o2[4] = {0.f, 0.f, 0.f, 0.f}, o3[4] = {0.f, 0.f, 0.f, 0.f};
            mma16816(o0, p[0], 0u, p[1], 0u, vb[0][0], vb[0][1]);
            mma16816(o1, p[0], 0u, p[1], 0u, vb[0][2], vb[0][3]);
            mma16816(o2, p[2], 0u, p[3], 0u, vb[1][0], vb[1][1]);
            mma16816(o3, p[2], 0u, p[3], 0u, vb[1][2], vb[1][3]);
            mma16816(o0, p[4], 0u, 0u, 0u, vb[2][0], vb[2][1]);
            mma16816(o1, p[4], 0u, 0u, 0u, vb[2][2], vb[2][3]);
            o0[0] += o2[0]; o0[1] += o2[1]; o1[0] += o3[0]; o1[1] += o3[1];
            *reinterpret_cast<uint32_t*>(smem + SM_O + g * RB + (16 * w + 2 * j) * 2) = pack_bf16(o0[0], o0[1]);
            *reinterpret_cast<uint32_t*>(smem + SM_O + g * RB + (16 * w + 8 + 2 * j) * 2) = pack_bf16(o1[0], o1[1]);
        }
        __syncthreads();
        PROF(7);
        PROF(8);
        {
            uint32_t ob[8][2];
            const uint32_t oa = sb + SM_O + (lane & 7) * RB + (lane >> 3) * 16;
#pragma unroll
            for (int i2 = 0; i2 < 4; i2++) ldsm_x4(ob[2 * i2][0], ob[2 * i2][1], ob[2 * i2 + 1][0], ob[2 * i2 + 1][1], oa + i2 * 64);
            PROF(9);
            float c0[3][4], c1[3][4];
#pragma unroll
            for (int q = 0; q < 3; q++)
#pragma unroll
                for (int e = 0; e < 4; e++) c0[q][e] = c1[q][e] = 0.f;
            const int t2 = three ? w + 16 : w;
#pragma unroll
            for (int i = 0; i < 8; i += 2) {
#pragma unroll
                for (int q = 0; q < 3; q++) {
                    const int t = q == 0 ? w : (q == 1 ? w + 8 : t2);
                    uint4 a = *reinterpret_cast<const uint4*>(smem + SM_WO + (t * 8 + i) * 512 + lane * 16);
                    uint4 a2 = *reinterpret_cast<const uint4*>(smem + SM_WO + (t * 8 + i + 1) * 512 + lane * 16);
                    mma16816(c0[q], a.x, a.y, a.z, a.w, ob[i][0], ob[i][1]);
                    mma16816(c1[q], a2.x, a2.y, a2.z, a2.w, ob[i + 1][0], ob[i + 1][1]);
                }
            }
            PROF(10);
            const bool odd = g & 1;
            float* dp = g_memacc + (size_t)(s + 1) * MT_ * D_ + (2 * j + (odd ? 1 : 0)) * D_ + (tile0 + w) * 16 + 4 * (g >> 1);
#pragma unroll
            for (int q = 0; q < 3; q++) {
#pragma unroll
                for (int e = 0; e < 4; e++) c0[q][e] += c1[q][e];
                float r1 = __shfl_xor_sync(0xffffffffu, odd ? c0[q][0] : c0[q][1], 4);
                float r2 = __shfl_xor_sync(0xffffffffu, odd ? c0[q][2] : c0[q][3], 4);
                float v0 = odd ? r1 : c0[q][0], v1 = odd ? c0[q][1] : r1, v2 = odd ? r2 : c0[q][2], v3 = odd ? c0[q][3] : r2;
                if (q < 2 || three)
                    asm volatile("red.global.add.v4.f32 [%0], {%1,%2,%3,%4};" ::"l"(dp + q * 128), "f"(v0), "f"(v1), "f"(v2), "f"(v3)
                                 : "memory");
            }
            PROF(11);
        }
        __syncthreads();
        if (tid == 0) {
            asm volatile("fence.acq_rel.gpu;" ::: "memory");
            asm volatile("red.relaxed.gpu.global.add.u32 [%0], 1;" ::"l"(g_cnt + ((s + 1) * 3 + rank) * 32) : "memory");
            if (rank != 0) asm volatile("red.relaxed.gpu.global.add.u32 [%0], 1;" ::"l"(g_prog + s * 32) : "memory");
        }
        prefetch_kv(s + 1);
    }
    TL_END(5);
    __syncthreads();
    if (tid == 0 && rank != 0) {
        __threadfence();
        asm volatile("red.relaxed.gpu.global.add.u32 [%0], 1;" ::"l"(g_prog + (NSEG_ - 1) * 32) : "memory");
    }
    cluster_arrive();
    cluster_wait();
}

__global__ void gate_kernel() {
    int guard = 0;
    while (ld_acquire(&g_resident[0]) < 96u && ++guard < (1 << 22)) __nanosleep(200);
}

constexpr int AT_PAIR = (32 + 40 + 48) * RB;
__global__ void __launch_bounds__(128) attn_kernel(int seg0) {
    extern __shared__ __align__(16) uint8_t smem[];
    const int tid = threadIdx.x, w = tid >> 5, lane = tid & 31, g = lane >> 2, j = lane & 3;
    const int pair = w >> 1, half = w & 1;
    const int unit = seg0 * 32 + blockIdx.x * 2 + pair;
    const int s = unit >> 5, h = unit & 31;
    TL_START(10 + seg0 / 4);
    if (tid == 0) {
        int guard = 0;
        while (ld_acquire(g_prog + s * 32) < 64u && ++guard < (1 << 22)) __nanosleep(400);
    }
    __syncthreads();
    uint8_t* base = smem + pair * AT_PAIR;
    const uint32_t sQ = smem_u32(base), sK = sQ + 32 * RB, sV = sK + 40 * RB;
    const int t64 = tid & 63;
    for (int idx = t64; idx < 112 * 16; idx += 64) {
        int r = idx >> 4, ch = idx & 15;
        const bf16* src;
        uint32_t dst;
        if (r < 32) {
            src = g_q + (size_t)(s * SEG_ + r) * HD_; dst = sQ + r * RB;
        } else if (r < 40) {
            src = g_km + (size_t)(s * MT_ + r - 32) * HD_; dst = sK + (r - 32) * RB;
        } else if (r < 72) {
            src = g_k + (size_t)(s * SEG_ + r - 40) * HD_; dst = sK + (r - 32) * RB;
        } else if (r < 80) {
            src = g_vm + (size_t)(s * MT_ + r - 72) * HD_; dst = sV + (r - 72) * RB;
        } else {
            src = g_v + (size_t)(s * SEG_ + r - 80) * HD_; dst = sV + (r - 72) * RB;
        }
        cp_async16(dst + ch * 16, src + h * DH_ + ch * 8);
    }
    cp_async_commit();
    for (int i = t64; i < 8 * RB / 4; i += 64) *reinterpret_cast<uint32_t*>(base + (32 + 40 + 40) * RB + i * 4) = 0u;
    cp_async_wait_all();
    __syncthreads();

    const float scale = 0.08838834764831845f;
    float sc[5][4];
#pragma unroll
    for (int t = 0; t < 5; t++) sc[t][0] = sc[t][1] = sc[t][2] = sc[t][3] = 0.f;
    const uint32_t qa = sQ + (16 * half + (lane & 15)) * RB + (lane >> 4) * 16;
    const uint32_t ka = sK + (lane & 7) * RB + (lane >> 3) * 16;
#pragma unroll
    for (int i2 = 0; i2 < 4; i2++) {
        uint32_t a[2][4];
        ldsm_x4(a[0][0], a[0][1], a[0][2], a[0][3], qa + i2 * 64);
        ldsm_x4(a[1][0], a[1][1], a[1][2], a[1][3], qa + i2 * 64 + 32);
#pragma unroll
        for (int t = 0; t < 5; t++) {
            uint32_t b0, b1, b2, b3;
            ldsm_x4(b0, b1, b2, b3, ka + t * 8 * RB + i2 * 64);
            mma16816(sc[t], a[0][0], a[0][1], a[0][2], a[0][3], b0, b1);
            mma16816(sc[t], a[1][0], a[1][1], a[1][2], a[1][3], b2, b3);
        }
    }
    const int r0 = 16 * half + g, r1 = r0 + 8;
    float m0 = -INFINITY, m1 = -INFINITY;
#pragma unroll
    for (int t = 0; t < 5; t++) {
#pragma unroll
        for (int e = 0; e < 2; e++) {
            const int kx = 8 * (t - 1) + 2 * j + e;
            float a = bf16r(bf16r(sc[t][e]) * scale), b = bf16r(bf16r(sc[t][2 + e]) * scale);
            if (t > 0 && kx > r0) a = -1e9f;
            if (t > 0 && kx > r1) b = -1e9f;
            sc[t][e] = a; sc[t][2 + e] = b;
            m0 = fmaxf(m0, a); m1 = fmaxf(m1, b);
        }
    }
    m0 = fmaxf(m0, __shfl_xor_sync(0xffffffffu, m0, 1)); m0 = fmaxf(m0, __shfl_xor_sync(0xffffffffu, m0, 2));
    m1 = fmaxf(m1, __shfl_xor_sync(0xffffffffu, m1, 1)); m1 = fmaxf(m1, __shfl_xor_sync(0xffffffffu, m1, 2));
    float l0 = 0.f, l1 = 0.f;
#pragma unroll
    for (int t = 0; t < 5; t++) {
#pragma unroll
        for (int e = 0; e < 2; e++) {
            sc[t][e] = __expf(sc[t][e] - m0); sc[t][2 + e] = __expf(sc[t][2 + e] - m1);
            l0 += sc[t][e]; l1 += sc[t][2 + e];
        }
    }
    l0 += __shfl_xor_sync(0xffffffffu, l0, 1); l0 += __shfl_xor_sync(0xffffffffu, l0, 2);
    l1 += __shfl_xor_sync(0xffffffffu, l1, 1); l1 += __shfl_xor_sync(0xffffffffu, l1, 2);
    const float i0 = 1.0f / l0, i1 = 1.0f / l1;
    uint32_t plo[5], phi[5];
#pragma unroll
    for (int t = 0; t < 5; t++) {
        plo[t] = pack_bf16(sc[t][0] * i0, sc[t][1] * i0);
        phi[t] = pack_bf16(sc[t][2] * i1, sc[t][3] * i1);
    }
    const uint32_t va = sV + (lane & 15) * RB + (lane >> 4) * 16;
    bf16* orow0 = g_o + (size_t)(s * SEG_ + r0) * HD_ + h * DH_ + 2 * j;
    bf16* orow1 = g_o + (size_t)(s * SEG_ + r1) * HD_ + h * DH_ + 2 * j;
#pragma unroll
    for (int n2 = 0; n2 < 8; n2++) {
        float o0[4] = {0.f, 0.f, 0.f, 0.f}, o1[4] = {0.f, 0.f, 0.f, 0.f};
#pragma unroll
        for (int i = 0; i < 3; i++) {
            uint32_t b00, b01, b10, b11;
            ldsm_x4_t(b00, b01, b10, b11, va + i * 16 * RB + n2 * 32);
            const uint32_t a0 = plo[2 * i], a1 = phi[2 * i];
            const uint32_t a2 = (i < 2) ? plo[i < 2 ? 2 * i + 1 : 0] : 0u, a3 = (i < 2) ? phi[i < 2 ? 2 * i + 1 : 0] : 0u;
            mma16816(o0, a0, a1, a2, a3, b00, b01);
            mma16816(o1, a0, a1, a2, a3, b10, b11);
        }
        *reinterpret_cast<uint32_t*>(orow0 + n2 * 16) = pack_bf16(o0[0], o0[1]);
        *reinterpret_cast<uint32_t*>(orow1 + n2 * 16) = pack_bf16(o0[2], o0[3]);
        *reinterpret_cast<uint32_t*>(orow0 + n2 * 16 + 8) = pack_bf16(o1[0], o1[1]);
        *reinterpret_cast<uint32_t*>(orow1 + n2 * 16 + 8) = pack_bf16(o1[2], o1[3]);
    }
    TL_END(10 + seg0 / 4);
}

typedef CUresult (*EncodeFn)(CUtensorMap*, CUtensorMapDataType, cuuint32_t, void*, const cuuint64_t*, const cuuint64_t*,
                             const cuuint32_t*, const cuuint32_t*, CUtensorMapInterleave, CUtensorMapSwizzle,
                             CUtensorMapL2promotion, CUtensorMapFloatOOBfill);

void make_map(EncodeFn fn, CUtensorMap* m, const void* ptr, uint64_t rows, uint64_t cols, uint32_t box_cols, uint32_t box_rows) {
    cuuint64_t dims[2] = {cols, rows};
    cuuint64_t strides[1] = {cols * 2};
    cuuint32_t box[2] = {box_cols, box_rows};
    cuuint32_t es[2] = {1, 1};
    fn(m, CU_TENSOR_MAP_DATA_TYPE_BFLOAT16, 2, const_cast<void*>(ptr), dims, strides, box, es, CU_TENSOR_MAP_INTERLEAVE_NONE,
       CU_TENSOR_MAP_SWIZZLE_128B, CU_TENSOR_MAP_L2_PROMOTION_L2_256B, CU_TENSOR_MAP_FLOAT_OOB_FILL_NONE);
}

struct HostState {
    bool init;
    const void* ptrs[4];
    CUtensorMap tmXn, tmWq, tmWk, tmWv, tmO, tmWo;
    EncodeFn fn;
    cudaStream_t side;
    cudaEvent_t evFork, evJoin;
};
HostState g_host;

}

extern "C" void kernel_launch(void* const* d_in, const int* in_sizes, int n_in, void* d_out, int out_size) {
    const bf16* A_x = (const bf16*)d_in[0];
    const bf16* A_mem0 = (const bf16*)d_in[1];
    const bf16* A_Wq = (const bf16*)d_in[2];
    const bf16* A_Wk = (const bf16*)d_in[3];
    const bf16* A_Wv = (const bf16*)d_in[4];
    const bf16* A_Wo = (const bf16*)d_in[5];
    const bf16* B_wr = (const bf16*)d_in[8];
    const bf16* B_wg = (const bf16*)d_in[9];
    const bf16* B_wu = (const bf16*)d_in[10];
    const bf16* B_wd = (const bf16*)d_in[11];
    bf16* out = (bf16*)d_out;

    constexpr int QKV_BN = 256, QKV_ST = 4, OUT_BN = 128, OUT_ST = 6;
    auto* qkv_fn = gemm_kernel<QKV_BN, QKV_ST, D_ / 64, 0>;
    auto* out_fn = gemm_kernel<OUT_BN, OUT_ST, HD_ / 64, 1>;

    HostState& hs = g_host;
    if (!hs.init) {
        void* fp = nullptr;
        cudaDriverEntryPointQueryResult qr;
        cudaGetDriverEntryPoint("cuTensorMapEncodeTiled", &fp, cudaEnableDefault, &qr);
        hs.fn = (EncodeFn)fp;
        cudaFuncSetAttribute(qkv_fn, cudaFuncAttributeMaxDynamicSharedMemorySize, GemmSmem<QKV_BN, QKV_ST>::TOTAL);
        cudaFuncSetAttribute(out_fn, cudaFuncAttributeMaxDynamicSharedMemorySize, GemmSmem<OUT_BN, OUT_ST>::TOTAL);
        cudaFuncSetAttribute(rec_kernel, cudaFuncAttributeMaxDynamicSharedMemorySize, SM_TOTAL);
        cudaFuncSetAttribute(attn_kernel, cudaFuncAttributeMaxDynamicSharedMemorySize, 2 * AT_PAIR);
        void *pxn, *po;
        cudaGetSymbolAddress(&pxn, g_xn);
        cudaGetSymbolAddress(&po, g_o);
        make_map(hs.fn, &hs.tmXn, pxn, S_, D_, 64, 128);
        make_map(hs.fn, &hs.tmO, po, S_, HD_, 64, 128);
        cudaStreamCreateWithFlags(&hs.side, cudaStreamNonBlocking);
        cudaEventCreateWithFlags(&hs.evFork, cudaEventDisableTiming);
        cudaEventCreateWithFlags(&hs.evJoin, cudaEventDisableTiming);
        hs.init = true;
    }
    if (hs.ptrs[0] != A_Wq || hs.ptrs[1] != A_Wk || hs.ptrs[2] != A_Wv || hs.ptrs[3] != A_Wo) {
        make_map(hs.fn, &hs.tmWq, A_Wq, D_, HD_, 64, 64);
        make_map(hs.fn, &hs.tmWk, A_Wk, D_, HD_, 64, 64);
        make_map(hs.fn, &hs.tmWv, A_Wv, D_, HD_, 64, 64);
        make_map(hs.fn, &hs.tmWo, A_Wo, HD_, D_, 64, 64);
        hs.ptrs[0] = A_Wq; hs.ptrs[1] = A_Wk; hs.ptrs[2] = A_Wv; hs.ptrs[3] = A_Wo;
    }

    constexpr int QKV_SM = GemmSmem<QKV_BN, QKV_ST>::TOTAL, OUT_SM = GemmSmem<OUT_BN, OUT_ST>::TOTAL;
    constexpr int NT = HD_ / QKV_BN;
    cudaStream_t mainS = cudaStreamPerThread, side = hs.side;
    ln_kernel<<<256, 256, 0, mainS>>>(A_x, B_wr, A_mem0);
    cudaEventRecord(hs.evFork, mainS);
    cudaStreamWaitEvent(side, hs.evFork, 0);
    qkv_fn<<<dim3(16, 2 * NT), 384, QKV_SM, mainS>>>(hs.tmXn, hs.tmWq, hs.tmWk, hs.tmWv, nullptr, nullptr, NT, 0);
    rec_kernel<<<96, 256, SM_TOTAL, mainS>>>(A_Wq, A_Wk, A_Wv, A_Wo);
    ffn1_kernel<<<112, 256, 0, side>>>(B_wg, B_wu);
    ffn2_kernel<<<64, 256, 0, side>>>(B_wd);
    gate_kernel<<<1, 1, 0, side>>>();
    qkv_fn<<<dim3(16, NT), 384, QKV_SM, side>>>(hs.tmXn, hs.tmWq, hs.tmWk, hs.tmWv, nullptr, nullptr, 0, 0);
    {
        const int chunk_mt[5] = {4, 4, 4, 2, 2};
        int mt0 = 0;
        for (int c = 0; c < 5; c++) {
            attn_kernel<<<chunk_mt[c] * 4 * H_ / 2, 128, 2 * AT_PAIR, side>>>(mt0 * 4);
            out_fn<<<dim3(chunk_mt[c], D_ / OUT_BN), 384, OUT_SM, side>>>(hs.tmO, hs.tmWo, hs.tmWo, hs.tmWo, A_x, out, 0, mt0);
            mt0 += chunk_mt[c];
        }
    }
    cudaEventRecord(hs.evJoin, side);
    cudaStreamWaitEvent(mainS, hs.evJoin, 0);
}
```

```cpp
#include <cuda_runtime.h>
#include <cuda_bf16.h>
#include <cuda.h>
#include <stdint.h>

typedef __nv_bfloat16 bf16;

namespace {

constexpr int S_ = 2048, D_ = 1024, H_ = 32, DH_ = 128, HD_ = 4096, MT_ = 8, SEG_ = 32, NSEG_ = 64, F_ = 3584;

__device__ __align__(1024) bf16 g_xn[S_ * D_];
__device__ __align__(1024) bf16 g_q[S_ * HD_];
__device__ __align__(1024) bf16 g_k[S_ * HD_];
__device__ __align__(1024) bf16 g_v[S_ * HD_];
__device__ __align__(1024) bf16 g_o[S_ * HD_];
__device__ __align__(1024) float g_memacc[NSEG_ * MT_ * D_];
__device__ __align__(1024) unsigned g_cnt[NSEG_ * 3 * 32];
__device__ __align__(128) unsigned g_resident[32];
__device__ __align__(1024) unsigned g_prog[NSEG_ * 32];
__device__ __align__(1024) bf16 g_km[NSEG_ * MT_ * HD_];
__device__ __align__(1024) bf16 g_vm[NSEG_ * MT_ * HD_];
__device__ __align__(1024) float g_part[256 * D_];
__device__ float g_r[S_];
__device__ float g_h[2 * F_];
__device__ float g_upd[2 * D_];
__device__ int g_idx[2];

__device__ __forceinline__ float bf16r(float x) { return __bfloat162float(__float2bfloat16_rn(x)); }
__device__ __forceinline__ uint32_t pack_bf16(float lo, float hi) {
    __nv_bfloat162 t = __floats2bfloat162_rn(lo, hi);
    return *reinterpret_cast<uint32_t*>(&t);
}
__device__ __forceinline__ float bf_lo(uint32_t u) { return __uint_as_float(u << 16); }
__device__ __forceinline__ float bf_hi(uint32_t u) { return __uint_as_float(u & 0xffff0000u); }
__device__ __forceinline__ uint32_t smem_u32(const void* p) { return (uint32_t)__cvta_generic_to_shared(p); }

__device__ __forceinline__ void mbar_init(uint32_t a, uint32_t cnt) {
    asm volatile("mbarrier.init.shared::cta.b64 [%0], %1;" ::"r"(a), "r"(cnt) : "memory");
}
__device__ __forceinline__ void mbar_expect_tx(uint32_t a, uint32_t bytes) {
    asm volatile("mbarrier.arrive.expect_tx.shared::cta.b64 _, [%0], %1;" ::"r"(a), "r"(bytes) : "memory");
}
__device__ __forceinline__ void mbar_wait(uint32_t a, uint32_t parity) {
    asm volatile(
        "{\n"
        ".reg .pred p;\n"
        "WAIT_%=:\n"
        "mbarrier.try_wait.parity.shared::cta.b64 p, [%0], %1;\n"
        "@p bra DONE_%=;\n"
        "bra WAIT_%=;\n"
        "DONE_%=:\n"
        "}\n" ::"r"(a), "r"(parity) : "memory");
}
__device__ __forceinline__ uint32_t mapa(uint32_t a, uint32_t rank) {
    uint32_t r;
    asm volatile("mapa.shared::cluster.u32 %0, %1, %2;" : "=r"(r) : "r"(a), "r"(rank));
    return r;
}
__device__ __forceinline__ void cluster_arrive() { asm volatile("barrier.cluster.arrive.release.aligned;" ::: "memory"); }
__device__ __forceinline__ void cluster_wait() { asm volatile("barrier.cluster.wait.acquire.aligned;" ::: "memory"); }
__device__ __forceinline__ uint32_t cluster_ctarank() {
    uint32_t r;
    asm volatile("mov.u32 %0, %%cluster_ctarank;" : "=r"(r));
    return r;
}
__device__ __forceinline__ void tma_load_2d(uint32_t dst, const CUtensorMap* map, uint32_t bar, int c0, int c1) {
    asm volatile(
        "cp.async.bulk.tensor.2d.shared::cluster.global.mbarrier::complete_tx::bytes [%0], [%1, {%3, %4}], [%2];" ::"r"(dst),
        "l"(map), "r"(bar), "r"(c0), "r"(c1)
        : "memory");
}
__device__ __forceinline__ void mma16816(float (&d)[4], uint32_t a0, uint32_t a1, uint32_t a2, uint32_t a3, uint32_t b0,
                                         uint32_t b1) {
    asm volatile(
        "mma.sync.aligned.m16n8k16.row.col.f32.bf16.bf16.f32 {%0,%1,%2,%3}, {%4,%5,%6,%7}, {%8,%9}, {%0,%1,%2,%3};"
        : "+f"(d[0]), "+f"(d[1]), "+f"(d[2]), "+f"(d[3])
        : "r"(a0), "r"(a1), "r"(a2), "r"(a3), "r"(b0), "r"(b1));
}
__device__ __forceinline__ void ldsm_x4(uint32_t& r0, uint32_t& r1, uint32_t& r2, uint32_t& r3, uint32_t a) {
    asm volatile("ldmatrix.sync.aligned.m8n8.x4.shared.b16 {%0,%1,%2,%3}, [%4];"
                 : "=r"(r0), "=r"(r1), "=r"(r2), "=r"(r3)
                 : "r"(a)
                 : "memory");
}
__device__ __forceinline__ void ldsm_x4_t(uint32_t& r0, uint32_t& r1, uint32_t& r2, uint32_t& r3, uint32_t a) {
    asm volatile("ldmatrix.sync.aligned.m8n8.x4.trans.shared.b16 {%0,%1,%2,%3}, [%4];"
                 : "=r"(r0), "=r"(r1), "=r"(r2), "=r"(r3)
                 : "r"(a)
                 : "memory");
}
__device__ __forceinline__ uint32_t movm_t(uint32_t a) {
    uint32_t d;
    asm volatile("movmatrix.sync.aligned.m8n8.trans.b16 %0, %1;" : "=r"(d) : "r"(a));
    return d;
}
__device__ __forceinline__ void cp_async16(uint32_t dst, const void* src) {
    asm volatile("cp.async.cg.shared.global [%0], [%1], 16;" ::"r"(dst), "l"(src) : "memory");
}
__device__ __forceinline__ void cp_async_commit() { asm volatile("cp.async.commit_group;" ::: "memory"); }
__device__ __forceinline__ void cp_async_wait_all() { asm volatile("cp.async.wait_all;" ::: "memory"); }

__global__ void __launch_bounds__(256) ln_kernel(const bf16* __restrict__ x, const bf16* __restrict__ w_r,
                                                 const bf16* __restrict__ mem0) {
    const int warp = threadIdx.x >> 5, lane = threadIdx.x & 31;
    const int row = blockIdx.x * 8 + warp;
    const uint4* xp = reinterpret_cast<const uint4*>(x + (size_t)row * D_);
    const uint4* wp = reinterpret_cast<const uint4*>(w_r);
    float v[32];
    float sum = 0.f;
#pragma unroll
    for (int c = 0; c < 4; c++) {
        uint4 u = xp[c * 32 + lane];
        uint32_t w[4] = {u.x, u.y, u.z, u.w};
#pragma unroll
        for (int i = 0; i < 4; i++) {
            v[c * 8 + 2 * i] = bf_lo(w[i]);
            v[c * 8 + 2 * i + 1] = bf_hi(w[i]);
            sum += v[c * 8 + 2 * i] + v[c * 8 + 2 * i + 1];
        }
    }
#pragma unroll
    for (int o = 16; o; o >>= 1) sum += __shfl_xor_sync(0xffffffffu, sum, o);
    const float mean = sum * (1.0f / D_);
    float sq = 0.f;
#pragma unroll
    for (int i = 0; i < 32; i++) {
        float d = v[i] - mean;
        sq += d * d;
    }
#pragma unroll
    for (int o = 16; o; o >>= 1) sq += __shfl_xor_sync(0xffffffffu, sq, o);
    const float mb = bf16r(mean);
    const float vb = bf16r(sq * (1.0f / D_));
    const float den = bf16r(sqrtf(bf16r(vb + 1e-5f)));
    float racc = 0.f;
    uint4* op = reinterpret_cast<uint4*>(g_xn + (size_t)row * D_);
#pragma unroll
    for (int c = 0; c < 4; c++) {
        uint4 wu = wp[c * 32 + lane];
        uint32_t ww[4] = {wu.x, wu.y, wu.z, wu.w};
        uint32_t o[4];
#pragma unroll
        for (int i = 0; i < 4; i++) {
            float a = bf16r(__fdiv_rn(bf16r(v[c * 8 + 2 * i] - mb), den));
            float b = bf16r(__fdiv_rn(bf16r(v[c * 8 + 2 * i + 1] - mb), den));
            racc += a * bf_lo(ww[i]) + b * bf_hi(ww[i]);
            o[i] = pack_bf16(a, b);
        }
        op[c * 32 + lane] = make_uint4(o[0], o[1], o[2], o[3]);
    }
#pragma unroll
    for (int o = 16; o; o >>= 1) racc += __shfl_xor_sync(0xffffffffu, racc, o);
    if (lane == 0) g_r[row] = bf16r(racc);

    {
        const int per = NSEG_ * MT_ * D_ / 256;
        float4* mp = reinterpret_cast<float4*>(g_memacc + (size_t)blockIdx.x * per);
        for (int i = threadIdx.x; i < per / 4; i += 256) {
            int e = blockIdx.x * per + i * 4;
            float4 z = make_float4(0.f, 0.f, 0.f, 0.f);
            if (e < MT_ * D_) {
                const int src = ((e >> 4) & 7) * D_ + (e >> 7) * 16 + (e & 15);
                z.x = __bfloat162float(mem0[src]);
                z.y = __bfloat162float(mem0[src + 1]);
                z.z = __bfloat162float(mem0[src + 2]);
                z.w = __bfloat162float(mem0[src + 3]);
            }
            mp[i] = z;
        }
        if (threadIdx.x < NSEG_ * 3 * 32 / 256) g_cnt[blockIdx.x * (NSEG_ * 3 * 32 / 256) + threadIdx.x] = 0u;
        if (threadIdx.x < NSEG_ * 32 / 256) g_prog[blockIdx.x * (NSEG_ * 32 / 256) + threadIdx.x] = 0u;
        if (blockIdx.x == 0 && threadIdx.x == 0) g_resident[0] = 0u;
        reinterpret_cast<float4*>(g_part)[blockIdx.x * 256 + threadIdx.x] = make_float4(0.f, 0.f, 0.f, 0.f);
    }
}

__device__ __forceinline__ void top2_block(int& i0, int& i1, float* sv, int* si) {
    const int tid = threadIdx.x;
    float b0 = -INFINITY, b1 = -INFINITY;
    int j0 = 0x7fffffff, j1 = 0x7fffffff;
    for (int t = tid; t < S_; t += 256) {
        float v = g_r[t];
        if (v > b0 || (v == b0 && t < j0)) {
            b1 = b0; j1 = j0; b0 = v; j0 = t;
        } else if (v > b1 || (v == b1 && t < j1)) {
            b1 = v; j1 = t;
        }
    }
    sv[tid * 2] = b0; si[tid * 2] = j0; sv[tid * 2 + 1] = b1; si[tid * 2 + 1] = j1;
    __syncthreads();
    if (tid < 32) {
        float c0 = -INFINITY, c1 = -INFINITY;
        int k0 = 0x7fffffff, k1 = 0x7fffffff;
        for (int t = tid; t < 512; t += 32) {
            float v = sv[t]; int id = si[t];
            if (v > c0 || (v == c0 && id < k0)) {
                c1 = c0; k1 = k0; c0 = v; k0 = id;
            } else if (v > c1 || (v == c1 && id < k1)) {
                c1 = v; k1 = id;
            }
        }
#pragma unroll
        for (int o = 16; o; o >>= 1) {
            float d0 = __shfl_xor_sync(0xffffffffu, c0, o), d1 = __shfl_xor_sync(0xffffffffu, c1, o);
            int e0 = __shfl_xor_sync(0xffffffffu, k0, o), e1 = __shfl_xor_sync(0xffffffffu, k1, o);
            bool dfirst = (d0 > c0) || (d0 == c0 && e0 < k0);
            float n0 = dfirst ? d0 : c0; int m0 = dfirst ? e0 : k0;
            float a = dfirst ? c0 : d0; int ai = dfirst ? k0 : e0;
            float b = dfirst ? d1 : c1; int bi = dfirst ? e1 : k1;
            bool afirst = (a > b) || (a == b && ai < bi);
            c0 = n0; k0 = m0; c1 = afirst ? a : b; k1 = afirst ? ai : bi;
        }
        if (tid == 0) { si[0] = k0; si[1] = k1; }
    }
    __syncthreads();
    i0 = si[0]; i1 = si[1];
    __syncthreads();
}

__global__ void __launch_bounds__(256) ffn1_kernel(const bf16* __restrict__ wg, const bf16* __restrict__ wu) {
    __shared__ float sv[512];
    __shared__ int si[512];
    __shared__ float sx[2][D_];
    __shared__ float red[64][4][33];
    int i0, i1;
    top2_block(i0, i1, sv, si);
    const int tid = threadIdx.x;
    if (blockIdx.x == 0 && tid == 0) { g_idx[0] = i0; g_idx[1] = i1; }
    for (int t = tid; t < D_; t += 256) {
        sx[0][t] = __bfloat162float(g_xn[(size_t)i0 * D_ + t]);
        sx[1][t] = __bfloat162float(g_xn[(size_t)i1 * D_ + t]);
    }
    __syncthreads();
    const int cq = tid & 3, rg = tid >> 2;
    const int col0 = blockIdx.x * 32 + cq * 8;
    float acc[4][8];
#pragma unroll
    for (int a = 0; a < 4; a++)
#pragma unroll
        for (int b = 0; b < 8; b++) acc[a][b] = 0.f;
#pragma unroll 4
    for (int p = 0; p < 16; p++) {
        int d = p * 64 + rg;
        uint4 ug = __ldg(reinterpret_cast<const uint4*>(wg + (size_t)d * F_ + col0));
        uint4 uu = __ldg(reinterpret_cast<const uint4*>(wu + (size_t)d * F_ + col0));
        float x0 = sx[0][d], x1 = sx[1][d];
        uint32_t a[4] = {ug.x, ug.y, ug.z, ug.w}, b[4] = {uu.x, uu.y, uu.z, uu.w};
#pragma unroll
        for (int i = 0; i < 4; i++) {
            acc[0][2 * i] += x0 * bf_lo(a[i]); acc[0][2 * i + 1] += x0 * bf_hi(a[i]);
            acc[1][2 * i] += x1 * bf_lo(a[i]); acc[1][2 * i + 1] += x1 * bf_hi(a[i]);
            acc[2][2 * i] += x0 * bf_lo(b[i]); acc[2][2 * i + 1] += x0 * bf_hi(b[i]);
            acc[3][2 * i] += x1 * bf_lo(b[i]); acc[3][2 * i + 1] += x1 * bf_hi(b[i]);
        }
    }
#pragma unroll
    for (int a = 0; a < 4; a++)
#pragma unroll
        for (int b = 0; b < 8; b++) red[rg][a][cq * 8 + b] = acc[a][b];
    __syncthreads();
    if (tid < 128) {
        int a = tid >> 5, c = tid & 31;
        float s = 0.f;
        for (int r = 0; r < 64; r++) s += red[r][a][c];
        red[0][a][c] = bf16r(s);
    }
    __syncthreads();
    if (tid < 64) {
        int tk = tid >> 5, c = tid & 31;
        float g = red[0][tk][c], u = red[0][2 + tk][c];
        float sg = bf16r(g / (1.0f + __expf(-g)));
        g_h[tk * F_ + blockIdx.x * 32 + c] = bf16r(sg * u);
    }
}

__global__ void __launch_bounds__(256) ffn2_kernel(const bf16* __restrict__ wd) {
    __shared__ float sh[2][F_];
    __shared__ float red[128][2][17];
    const int tid = threadIdx.x;
    for (int t = tid; t < 2 * F_; t += 256) (&sh[0][0])[t] = g_h[t];
    __syncthreads();
    const int ch = tid & 1, rg = tid >> 1;
    const int col0 = blockIdx.x * 16 + ch * 8;
    float acc[2][8];
#pragma unroll
    for (int b = 0; b < 8; b++) acc[0][b] = acc[1][b] = 0.f;
#pragma unroll 7
    for (int p = 0; p < 28; p++) {
        int f = p * 128 + rg;
        uint4 u = __ldg(reinterpret_cast<const uint4*>(wd + (size_t)f * D_ + col0));
        float h0 = sh[0][f], h1 = sh[1][f];
        uint32_t a[4] = {u.x, u.y, u.z, u.w};
#pragma unroll
        for (int i = 0; i < 4; i++) {
            acc[0][2 * i] += h0 * bf_lo(a[i]); acc[0][2 * i + 1] += h0 * bf_hi(a[i]);
            acc[1][2 * i] += h1 * bf_lo(a[i]); acc[1][2 * i + 1] += h1 * bf_hi(a[i]);
        }
    }
#pragma unroll
    for (int b = 0; b < 8; b++) { red[rg][0][ch * 8 + b] = acc[0][b]; red[rg][1][ch * 8 + b] = acc[1][b]; }
    __syncthreads();
    if (tid < 32) {
        int tk = tid >> 4, c = tid & 15;
        float s = 0.f;
        for (int r = 0; r < 128; r++) s += red[r][tk][c];
        float y = bf16r(s);
        float rv = g_r[g_idx[tk]];
        float sg = bf16r(1.0f / (1.0f + __expf(-rv)));
        g_upd[tk * D_ + blockIdx.x * 16 + c] = bf16r(y * sg);
    }
}

__device__ __forceinline__ uint64_t make_desc(uint32_t addr, uint32_t lbo_bytes, uint32_t sbo_bytes) {
    return (uint64_t)((addr & 0x3FFFF) >> 4) | ((uint64_t)(lbo_bytes >> 4) << 16) | ((uint64_t)(sbo_bytes >> 4) << 32) |
           (1ull << 62);
}
__device__ __forceinline__ void wgmma_fence() { asm volatile("wgmma.fence.sync.aligned;" ::: "memory"); }
__device__ __forceinline__ void wgmma_commit() { asm volatile("wgmma.commit_group.sync.aligned;" ::: "memory"); }
template <int N>
__device__ __forceinline__ void wgmma_wait() { asm volatile("wgmma.wait_group.sync.aligned %0;" ::"n"(N) : "memory"); }

#define ACC8(b) "+f"(d[b]), "+f"(d[b + 1]), "+f"(d[b + 2]), "+f"(d[b + 3]), "+f"(d[b + 4]), "+f"(d[b + 5]), "+f"(d[b + 6]), "+f"(d[b + 7])
#define ACC32(b) ACC8(b), ACC8(b + 8), ACC8(b + 16), ACC8(b + 24)

__device__ __forceinline__ void wgmma_n128(float (&d)[64], uint64_t da, uint64_t db, int scale_d) {
    asm volatile(
        "{\n.reg .pred p;\nsetp.ne.b32 p, %66, 0;\n"
        "wgmma.mma_async.sync.aligned.m64n128k16.f32.bf16.bf16 "
        "{%0,%1,%2,%3,%4,%5,%6,%7,%8,%9,%10,%11,%12,%13,%14,%15,%16,%17,%18,%19,%20,%21,%22,%23,%24,%25,%26,%27,%28,%29,%30,%31,"
        "%32,%33,%34,%35,%36,%37,%38,%39,%40,%41,%42,%43,%44,%45,%46,%47,%48,%49,%50,%51,%52,%53,%54,%55,%56,%57,%58,%59,%60,%61,%62,%63},"
        " %64, %65, p, 1, 1, 0, 1;\n}\n"
        : ACC32(0), ACC32(32)
        : "l"(da), "l"(db), "r"(scale_d));
}
__device__ __forceinline__ void wgmma_n256(float (&d)[128], uint64_t da, uint64_t db, int scale_d) {
    asm volatile(
        "{\n.reg .pred p;\nsetp.ne.b32 p, %130, 0;\n"
        "wgmma.mma_async.sync.aligned.m64n256k16.f32.bf16.bf16 "
        "{%0,%1,%2,%3,%4,%5,%6,%7,%8,%9,%10,%11,%12,%13,%14,%15,%16,%17,%18,%19,%20,%21,%22,%23,%24,%25,%26,%27,%28,%29,%30,%31,"
        "%32,%33,%34,%35,%36,%37,%38,%39,%40,%41,%42,%43,%44,%45,%46,%47,%48,%49,%50,%51,%52,%53,%54,%55,%56,%57,%58,%59,%60,%61,%62,%63,"
        "%64,%65,%66,%67,%68,%69,%70,%71,%72,%73,%74,%75,%76,%77,%78,%79,%80,%81,%82,%83,%84,%85,%86,%87,%88,%89,%90,%91,%92,%93,%94,%95,"
        "%96,%97,%98,%99,%100,%101,%102,%103,%104,%105,%106,%107,%108,%109,%110,%111,%112,%113,%114,%115,%116,%117,%118,%119,%120,%121,%122,%123,%124,%125,%126,%127},"
        " %128, %129, p, 1, 1, 0, 1;\n}\n"
        : ACC32(0), ACC32(32), ACC32(64), ACC32(96)
        : "l"(da), "l"(db), "r"(scale_d));
}

template <int BN, int STAGES>
struct GemmSmem {
    static constexpr int A_BYTES = 128 * 64 * 2;
    static constexpr int B_BYTES = BN * 64 * 2;
    static constexpr int STAGE_BYTES = A_BYTES + B_BYTES;
    static constexpr int TOTAL = STAGES * STAGE_BYTES + 1024   + 256  ;
};

template <int BN, int STAGES, int KT, int EPI>
__global__ void __launch_bounds__(384, 1)
    gemm_kernel(const __grid_constant__ CUtensorMap tmA, const __grid_constant__ CUtensorMap tmB0,
                const __grid_constant__ CUtensorMap tmB1, const __grid_constant__ CUtensorMap tmB2,
                const bf16* __restrict__ xin, bf16* __restrict__ out, int n_tile_base, int m_tile_base) {
    using L = GemmSmem<BN, STAGES>;
    extern __shared__ uint8_t smem_raw[];
    const uint32_t sbase = (smem_u32(smem_raw) + 1023u) & ~1023u;
    const uint32_t bar_base = sbase + STAGES * L::STAGE_BYTES;
    auto full_bar = [&](int s) { return bar_base + s * 8; };
    auto empty_bar = [&](int s) { return bar_base + 64 + s * 8; };
    const int tid = threadIdx.x, wg = tid >> 7;
    const int m0 = (blockIdx.x + m_tile_base) * 128;
    const int ntile = blockIdx.y + n_tile_base;
    const int k0 = (EPI == 2) ? blockIdx.z * KT * 64 : 0;

    if (tid == 0) {
        for (int s = 0; s < STAGES; s++) {
            mbar_init(full_bar(s), 1);
            mbar_init(empty_bar(s), 2);
        }
        asm volatile("fence.mbarrier_init.release.cluster;" ::: "memory");
    }
    __syncthreads();

    if (wg == 0) {
        asm volatile("setmaxnreg.dec.sync.aligned.u32 40;");
        if (tid == 0) {
            const CUtensorMap* tb;
            int n0;
            if (EPI == 0) {
                const int which = ntile / (HD_ / BN);
                tb = which == 0 ? &tmB0 : (which == 1 ? &tmB1 : &tmB2);
                n0 = (ntile % (HD_ / BN)) * BN;
            } else {
                tb = &tmB0;
                n0 = ntile * BN;
            }
            for (int kt = 0; kt < KT; kt++) {
                const int s = kt % STAGES;
                const uint32_t ph = (kt / STAGES) & 1;
                mbar_wait(empty_bar(s), ph ^ 1);
                mbar_expect_tx(full_bar(s), L::STAGE_BYTES);
                const uint32_t sa = sbase + s * L::STAGE_BYTES;
                tma_load_2d(sa, &tmA, full_bar(s), k0 + kt * 64, m0);
#pragma unroll
                for (int box = 0; box < BN / 64; box++)
                    tma_load_2d(sa + L::A_BYTES + box * 8192, tb, full_bar(s), n0 + box * 64, k0 + kt * 64);
            }
        }
    } else {
        asm volatile("setmaxnreg.inc.sync.aligned.u32 232;");
        const int cw = wg - 1;
        float acc[BN / 2];
        for (int kt = 0; kt < KT; kt++) {
            const int s = kt % STAGES;
            const uint32_t ph = (kt / STAGES) & 1;
            mbar_wait(full_bar(s), ph);
            const uint32_t sa = sbase + s * L::STAGE_BYTES + cw * 8192;
            const uint32_t sb = sbase + s * L::STAGE_BYTES + L::A_BYTES;
            wgmma_fence();
#pragma unroll
            for (int kk = 0; kk < 4; kk++) {
                uint64_t da = make_desc(sa + kk * 32, 16, 1024);
                uint64_t db = make_desc(sb + kk * 2048, 8192, 1024);
                if constexpr (BN == 256) wgmma_n256(acc, da, db, (kt | kk) != 0);
                else wgmma_n128(acc, da, db, (kt | kk) != 0);
            }
            wgmma_commit();
            if (kt > 0) {
                wgmma_wait<1>();
                if ((tid & 127) == 0) {
                    const int ps = (kt - 1) % STAGES;
                    asm volatile("mbarrier.arrive.shared::cta.b64 _, [%0];" ::"r"(empty_bar(ps)) : "memory");
                }
            }
        }
        wgmma_wait<0>();
        if constexpr (EPI == 2) {
            const int wq2 = (tid >> 5) & 3, l2 = tid & 31;
            float* pp = g_part + (size_t)(blockIdx.x * 128 + cw * 64 + wq2 * 16 + (l2 >> 2)) * D_ + ntile * BN + 2 * (l2 & 3);
#pragma unroll
            for (int c = 0; c < BN / 8; c++) {
                asm volatile("red.global.add.v2.f32 [%0], {%1,%2};" ::"l"(pp + c * 8), "f"(acc[c * 4]), "f"(acc[c * 4 + 1]) : "memory");
                asm volatile("red.global.add.v2.f32 [%0], {%1,%2};" ::"l"(pp + 8 * D_ + c * 8), "f"(acc[c * 4 + 2]), "f"(acc[c * 4 + 3]) : "memory");
            }
            return;
        }
        asm volatile("bar.sync 1, 256;" ::: "memory");
        constexpr int ROWB = BN * 2 + 16;
        const uint32_t stg = sbase + cw * (64 * ROWB);
        const int wq = (tid >> 5) & 3, lane = tid & 31, g = lane >> 2, j = lane & 3;
#pragma unroll
        for (int c = 0; c < BN / 8; c++) {
            uint32_t lo = pack_bf16(acc[c * 4], acc[c * 4 + 1]);
            uint32_t hi = pack_bf16(acc[c * 4 + 2], acc[c * 4 + 3]);
            uint32_t a0 = stg + (wq * 16 + g) * ROWB + c * 16 + j * 4;
            asm volatile("st.shared.b32 [%0], %1;" ::"r"(a0), "r"(lo) : "memory");
            asm volatile("st.shared.b32 [%0], %1;" ::"r"(a0 + 8 * ROWB), "r"(hi) : "memory");
        }
        __syncwarp();
        constexpr int CPR = BN / 8;
        if (EPI == 0) {
            const int which = ntile / (HD_ / BN);
            bf16* dst = which == 0 ? g_q : (which == 1 ? g_k : g_v);
            const int n0 = (ntile % (HD_ / BN)) * BN;
#pragma unroll
            for (int it = 0; it < 16 * CPR / 32; it++) {
                int idx = it * 32 + lane;
                int r = idx / CPR, ch = idx % CPR;
                uint4 v;
                asm volatile("ld.shared.v4.b32 {%0,%1,%2,%3}, [%4];"
                             : "=r"(v.x), "=r"(v.y), "=r"(v.z), "=r"(v.w)
                             : "r"(stg + (wq * 16 + r) * ROWB + ch * 16));
                int row = m0 + cw * 64 + wq * 16 + r;
                *reinterpret_cast<uint4*>(dst + (size_t)row * HD_ + n0 + ch * 8) = v;
            }
        } else {
            const int n0 = ntile * BN;
            const int i0 = g_idx[0], i1 = g_idx[1];
#pragma unroll
            for (int it = 0; it < 16 * CPR / 32; it++) {
                int idx = it * 32 + lane;
                int r = idx / CPR, ch = idx % CPR;
                uint4 v;
                asm volatile("ld.shared.v4.b32 {%0,%1,%2,%3}, [%4];"
                             : "=r"(v.x), "=r"(v.y), "=r"(v.z), "=r"(v.w)
                             : "r"(stg + (wq * 16 + r) * ROWB + ch * 16));
                int row = m0 + cw * 64 + wq * 16 + r;
                size_t off = (size_t)row * D_ + n0 + ch * 8;
                uint4 xv = __ldg(reinterpret_cast<const uint4*>(xin + off));
                uint4 nv = *reinterpret_cast<const uint4*>(g_xn + off);
                uint32_t av[4] = {v.x, v.y, v.z, v.w}, xa[4] = {xv.x, xv.y, xv.z, xv.w}, na[4] = {nv.x, nv.y, nv.z, nv.w};
                uint32_t ov[4];
                const float* up = (row == i0) ? (g_upd + n0 + ch * 8) : ((row == i1) ? (g_upd + D_ + n0 + ch * 8) : nullptr);
#pragma unroll
                for (int i = 0; i < 4; i++) {
                    float b0 = bf_lo(na[i]), b1 = bf_hi(na[i]);
                    if (up) { b0 = bf16r(b0 + up[2 * i]); b1 = bf16r(b1 + up[2 * i + 1]); }
                    float t0 = bf16r(bf_lo(xa[i]) + bf_lo(av[i])), t1 = bf16r(bf_hi(xa[i]) + bf_hi(av[i]));
                    ov[i] = pack_bf16(t0 + b0, t1 + b1);
                }
                *reinterpret_cast<uint4*>(out + off) = make_uint4(ov[0], ov[1], ov[2], ov[3]);
            }
        }
    }
}

__global__ void __launch_bounds__(128) fin_kernel(const bf16* __restrict__ xin, bf16* __restrict__ out, int row0) {
    const int row = row0 + blockIdx.x, c = threadIdx.x * 8;
    const size_t off = (size_t)row * D_ + c;
    const float4 a0 = __ldcg(reinterpret_cast<const float4*>(g_part + (size_t)blockIdx.x * D_ + c));
    const float4 a1 = __ldcg(reinterpret_cast<const float4*>(g_part + (size_t)blockIdx.x * D_ + c + 4));
    const float av[8] = {a0.x, a0.y, a0.z, a0.w, a1.x, a1.y, a1.z, a1.w};
    const uint4 xv = __ldg(reinterpret_cast<const uint4*>(xin + off));
    const uint4 nv = *reinterpret_cast<const uint4*>(g_xn + off);
    const uint32_t xa[4] = {xv.x, xv.y, xv.z, xv.w}, na[4] = {nv.x, nv.y, nv.z, nv.w};
    const float* up = (row == g_idx[0]) ? (g_upd + c) : ((row == g_idx[1]) ? (g_upd + D_ + c) : nullptr);
    uint32_t ov[4];
#pragma unroll
    for (int i = 0; i < 4; i++) {
        float b0 = bf_lo(na[i]), b1 = bf_hi(na[i]);
        if (up) { b0 = bf16r(b0 + up[2 * i]); b1 = bf16r(b1 + up[2 * i + 1]); }
        float t0 = bf16r(bf_lo(xa[i]) + bf16r(av[2 * i])), t1 = bf16r(bf_hi(xa[i]) + bf16r(av[2 * i + 1]));
        ov[i] = pack_bf16(t0 + b0, t1 + b1);
    }
    *reinterpret_cast<uint4*>(out + off) = make_uint4(ov[0], ov[1], ov[2], ov[3]);
}

constexpr int NRF = 44;
constexpr int RB = 272;
constexpr int SM_WSM = 0;
constexpr int SM_WO = SM_WSM + (64 - NRF) * 8 * 512;
constexpr int SM_PART = SM_WO + 22 * 8 * 512;
constexpr int SM_Q = SM_PART + 8 * 8 * 132 * 4;
constexpr int SM_K = SM_Q + 8 * RB;
constexpr int SM_V = SM_K + 40 * RB;
constexpr int SM_XBAR = SM_V + 48 * RB;
constexpr int SM_TOTAL = SM_XBAR + 16;
constexpr int SM_O = SM_PART;
constexpr int SM_S = SM_PART + 8 * RB;

__device__ __forceinline__ float4 ld_poll4(const float4* p) {
    float4 v;
    asm volatile("ld.relaxed.gpu.global.v4.f32 {%0,%1,%2,%3}, [%4];" : "=f"(v.x), "=f"(v.y), "=f"(v.z), "=f"(v.w) : "l"(p) : "memory");
    return v;
}
__device__ __forceinline__ unsigned ld_acquire(const unsigned* p) {
    unsigned v;
    asm volatile("ld.acquire.gpu.global.u32 %0, [%1];" : "=r"(v) : "l"(p) : "memory");
    return v;
}

__global__ void __cluster_dims__(3, 1, 1) __launch_bounds__(256, 1)
    rec_kernel(const bf16* __restrict__ Wq, const bf16* __restrict__ Wk, const bf16* __restrict__ Wv,
               const bf16* __restrict__ Wo) {
    extern __shared__ __align__(1024) uint8_t smem[];
    const uint32_t sb = smem_u32(smem);
    const int tid = threadIdx.x, w = tid >> 5, lane = tid & 31, g = lane >> 2, j = lane & 3;
    const uint32_t rank = cluster_ctarank();
    const int h = blockIdx.x / 3;
    const bf16* W = rank == 0 ? Wq : (rank == 1 ? Wk : Wv);
    const int tile0 = rank == 0 ? 0 : (rank == 1 ? 22 : 43);
    const int ntiles = rank == 0 ? 22 : 21;
    if (threadIdx.x == 0) atomicAdd(&g_resident[0], 1u);
    auto prefetch_kv = [&](int s) {
#pragma unroll
        for (int it = 0; it < 2; it++) {
            int idx = it * 256 + tid;
            int r = idx >> 4, ch = idx & 15;
            size_t off = (size_t)(s * SEG_ + r) * HD_ + h * DH_ + ch * 8;
            cp_async16(sb + SM_K + (8 + r) * RB + ch * 16, g_k + off);
            cp_async16(sb + SM_V + (8 + r) * RB + ch * 16, g_v + off);
        }
        cp_async_commit();
    };
    prefetch_kv(0);
    for (int i = tid; i < 8 * RB / 4; i += 256) *reinterpret_cast<uint32_t*>(smem + SM_V + 40 * RB + i * 4) = 0u;

    uint32_t wreg[NRF][4];
    {
        const int klo = 4 * (g >> 1) + (g & 1);
        const bf16* wbase = W + (size_t)(128 * w) * HD_ + h * DH_ + 2 * j;
#pragma unroll
        for (int f = 0; f < 64; f++) {
            const int i = f >> 3, mt = f & 7;
            const bf16* p = wbase + (size_t)(16 * i + klo) * HD_ + 16 * mt;
            uint32_t r0 = __ldg(reinterpret_cast<const uint32_t*>(p));
            uint32_t r1 = __ldg(reinterpret_cast<const uint32_t*>(p + 8));
            uint32_t r2 = __ldg(reinterpret_cast<const uint32_t*>(p + 2 * HD_));
            uint32_t r3 = __ldg(reinterpret_cast<const uint32_t*>(p + 2 * HD_ + 8));
            r0 = movm_t(r0); r1 = movm_t(r1); r2 = movm_t(r2); r3 = movm_t(r3);
            if (f < NRF) {
                wreg[f < NRF ? f : 0][0] = r0; wreg[f < NRF ? f : 0][1] = r1;
                wreg[f < NRF ? f : 0][2] = r2; wreg[f < NRF ? f : 0][3] = r3;
            } else {
                *reinterpret_cast<uint4*>(smem + SM_WSM + ((f - NRF) * 8 + w) * 512 + lane * 16) = make_uint4(r0, r1, r2, r3);
            }
        }
        for (int t = w; t < ntiles; t += 8) {
#pragma unroll
            for (int i = 0; i < 8; i++) {
                const bf16* p = Wo + (size_t)(h * DH_ + 16 * i + g) * D_ + (tile0 + t) * 16 + 4 * j;
                uint32_t r0 = __ldg(reinterpret_cast<const uint32_t*>(p));
                uint32_t r1 = __ldg(reinterpret_cast<const uint32_t*>(p + 2));
                uint32_t r2 = __ldg(reinterpret_cast<const uint32_t*>(p + 8 * D_));
                uint32_t r3 = __ldg(reinterpret_cast<const uint32_t*>(p + 8 * D_ + 2));
                r0 = movm_t(r0); r1 = movm_t(r1); r2 = movm_t(r2); r3 = movm_t(r3);
                *reinterpret_cast<uint4*>(smem + SM_WO + (t * 8 + i) * 512 + lane * 16) = make_uint4(r0, r1, r2, r3);
            }
        }
    }
    if (tid == 0) {
        mbar_init(sb + SM_XBAR, 1);
        asm volatile("fence.mbarrier_init.release.cluster;" ::: "memory");
    }
    __syncthreads();
    cluster_arrive();
    cluster_wait();

    const uint32_t dst_local = sb + (rank == 0 ? SM_Q : (rank == 1 ? SM_K : SM_V)) + w * RB + lane * 8;
    const uint32_t dst0 = mapa(dst_local, 0), dst1 = mapa(dst_local, 1), dst2 = mapa(dst_local, 2);
    const uint32_t xb0 = mapa(sb + SM_XBAR, 0), xb1 = mapa(sb + SM_XBAR, 1), xb2 = mapa(sb + SM_XBAR, 2);
    const bool three = w + 16 < ntiles;
    const int ra = w <= 2 ? 0 : (w <= 5 ? 1 : 2);
    const int rb2 = (w == 2) ? 1 : ((w == 5) ? 2 : ra);
    const float scale = 0.08838834764831845f;

    for (int s = 0; s < NSEG_; s++) {
        if (tid == 0) mbar_expect_tx(sb + SM_XBAR, 3 * 2048);
        if (s > 0) {
            if (lane < 2) {
                const unsigned* cp = g_cnt + (s * 3 + (lane == 0 ? ra : rb2)) * 32;
                int guard = 0;
                unsigned v;
                do {
                    asm volatile("ld.relaxed.gpu.global.u32 %0, [%1];" : "=r"(v) : "l"(cp) : "memory");
                } while (v < 32u && ++guard < (1 << 22));
            }
            __syncwarp();
        }
        uint32_t bf[16];
        {
            const float4* mp = reinterpret_cast<const float4*>(g_memacc + (size_t)s * MT_ * D_ + (8 * w) * 128 + g * 16 + 4 * j);
            float4 mv[8];
#pragma unroll
            for (int i = 0; i < 8; i++) mv[i] = ld_poll4(mp + 32 * i);
#pragma unroll
            for (int i = 0; i < 8; i++) {
                bf[2 * i] = pack_bf16(mv[i].x, mv[i].y);
                bf[2 * i + 1] = pack_bf16(mv[i].z, mv[i].w);
            }
        }
        float acc[8][4];
#pragma unroll
        for (int mt = 0; mt < 8; mt++) acc[mt][0] = acc[mt][1] = acc[mt][2] = acc[mt][3] = 0.f;
#pragma unroll
        for (int i = 0; i < 8; i++) {
            const uint32_t b0 = bf[2 * i], b1 = bf[2 * i + 1];
#pragma unroll
            for (int mt = 0; mt < 8; mt++) {
                const int f = i * 8 + mt;
                if (f < NRF) {
                    mma16816(acc[mt], wreg[f < NRF ? f : 0][0], wreg[f < NRF ? f : 0][1], wreg[f < NRF ? f : 0][2],
                             wreg[f < NRF ? f : 0][3], b0, b1);
                } else {
                    uint4 a = *reinterpret_cast<const uint4*>(smem + SM_WSM + ((f - NRF) * 8 + w) * 512 + lane * 16);
                    mma16816(acc[mt], a.x, a.y, a.z, a.w, b0, b1);
                }
            }
        }
        {
            float* pp = reinterpret_cast<float*>(smem + SM_PART) + w * (8 * 132);
#pragma unroll
            for (int mt = 0; mt < 8; mt++) {
                pp[(2 * j) * 132 + 16 * mt + g] = acc[mt][0];
                pp[(2 * j + 1) * 132 + 16 * mt + g] = acc[mt][1];
                pp[(2 * j) * 132 + 16 * mt + g + 8] = acc[mt][2];
                pp[(2 * j + 1) * 132 + 16 * mt + g + 8] = acc[mt][3];
            }
        }
        cp_async_wait_all();
        __syncthreads();
        {
            const float* pp = reinterpret_cast<const float*>(smem + SM_PART) + w * 132 + 4 * lane;
            float4 t = *reinterpret_cast<const float4*>(pp);
#pragma unroll
            for (int q = 1; q < 8; q++) {
                float4 u = *reinterpret_cast<const float4*>(pp + q * (8 * 132));
                t.x += u.x; t.y += u.y; t.z += u.z; t.w += u.w;
            }
            const uint32_t lo = pack_bf16(t.x, t.y), hi = pack_bf16(t.z, t.w);
            asm volatile("st.async.weak.shared::cluster.mbarrier::complete_tx::bytes.v2.b32 [%0], {%1,%2}, [%3];" ::"r"(dst0), "r"(lo), "r"(hi), "r"(xb0) : "memory");
            asm volatile("st.async.weak.shared::cluster.mbarrier::complete_tx::bytes.v2.b32 [%0], {%1,%2}, [%3];" ::"r"(dst1), "r"(lo), "r"(hi), "r"(xb1) : "memory");
            asm volatile("st.async.weak.shared::cluster.mbarrier::complete_tx::bytes.v2.b32 [%0], {%1,%2}, [%3];" ::"r"(dst2), "r"(lo), "r"(hi), "r"(xb2) : "memory");
            if (rank != 0) {
                bf16* gp = (rank == 1 ? g_km : g_vm) + (size_t)(s * MT_ + w) * HD_ + h * DH_ + 4 * lane;
                *reinterpret_cast<uint2*>(gp) = make_uint2(lo, hi);
            }
        }
        uint4 wpre[8];
#pragma unroll
        for (int i = 0; i < 8; i++) wpre[i] = *reinterpret_cast<const uint4*>(smem + SM_WO + (w * 8 + i) * 512 + lane * 16);
        mbar_wait(sb + SM_XBAR, s & 1);
        if (s == NSEG_ - 1) break;
        if (w < 5) {
            float c0[4] = {0.f, 0.f, 0.f, 0.f}, c1[4] = {0.f, 0.f, 0.f, 0.f};
            const uint32_t qa = sb + SM_Q + (lane & 7) * RB + (lane >> 3) * 16;
            const uint32_t ka = sb + SM_K + (8 * w + (lane & 7)) * RB + (lane >> 3) * 16;
#pragma unroll
            for (int i2 = 0; i2 < 4; i2++) {
                uint32_t a0, a2, a0n, a2n, b0, b1, b0n, b1n;
                ldsm_x4(a0, a2, a0n, a2n, qa + i2 * 64);
                ldsm_x4(b0, b1, b0n, b1n, ka + i2 * 64);
                mma16816(c0, a0, 0u, a2, 0u, b0, b1);
                mma16816(c1, a0n, 0u, a2n, 0u, b0n, b1n);
            }
            float s0 = bf16r(bf16r(c0[0] + c1[0]) * scale), s1 = bf16r(bf16r(c0[1] + c1[1]) * scale);
            *reinterpret_cast<float2*>(smem + SM_S + (g * 40 + 8 * w + 2 * j) * 4) = make_float2(s0, s1);
        }
        __syncthreads();
        {
            const uint32_t va = sb + SM_V + (lane & 15) * RB + (16 * w + (lane >> 4) * 8) * 2;
            uint32_t vb[3][4];
#pragma unroll
            for (int i = 0; i < 3; i++) ldsm_x4_t(vb[i][0], vb[i][1], vb[i][2], vb[i][3], va + i * 16 * RB);
            float sv[5][2];
            float mx = -INFINITY;
#pragma unroll
            for (int t = 0; t < 5; t++) {
                float2 u = *reinterpret_cast<const float2*>(smem + SM_S + (g * 40 + 8 * t + 2 * j) * 4);
                sv[t][0] = u.x; sv[t][1] = u.y;
                mx = fmaxf(mx, fmaxf(u.x, u.y));
            }
            mx = fmaxf(mx, __shfl_xor_sync(0xffffffffu, mx, 1));
            mx = fmaxf(mx, __shfl_xor_sync(0xffffffffu, mx, 2));
            float sum = 0.f;
#pragma unroll
            for (int t = 0; t < 5; t++) {
                sv[t][0] = __expf(sv[t][0] - mx); sv[t][1] = __expf(sv[t][1] - mx);
                sum += sv[t][0] + sv[t][1];
            }
            sum += __shfl_xor_sync(0xffffffffu, sum, 1);
            sum += __shfl_xor_sync(0xffffffffu, sum, 2);
            const float inv = __frcp_rn(sum);
            uint32_t p[5];
#pragma unroll
            for (int t = 0; t < 5; t++) p[t] = pack_bf16(sv[t][0] * inv, sv[t][1] * inv);
            float o0[4] = {0.f, 0.f, 0.f, 0.f}, o1[4] = {0.f, 0.f, 0.f, 0.f};
            float o2[4] = {0.f, 0.f, 0.f, 0.f}, o3[4] = {0.f, 0.f, 0.f, 0.f};
            mma16816(o0, p[0], 0u, p[1], 0u, vb[0][0], vb[0][1]);
            mma16816(o1, p[0], 0u, p[1], 0u, vb[0][2], vb[0][3]);
            mma16816(o2, p[2], 0u, p[3], 0u, vb[1][0], vb[1][1]);
            mma16816(o3, p[2], 0u, p[3], 0u, vb[1][2], vb[1][3]);
            mma16816(o0, p[4], 0u, 0u, 0u, vb[2][0], vb[2][1]);
            mma16816(o1, p[4], 0u, 0u, 0u, vb[2][2], vb[2][3]);
            o0[0] += o2[0]; o0[1] += o2[1]; o1[0] += o3[0]; o1[1] += o3[1];
            *reinterpret_cast<uint32_t*>(smem + SM_O + g * RB + (16 * w + 2 * j) * 2) = pack_bf16(o0[0], o0[1]);
            *reinterpret_cast<uint32_t*>(smem + SM_O + g * RB + (16 * w + 8 + 2 * j) * 2) = pack_bf16(o1[0], o1[1]);
        }
        __syncthreads();
        {
            uint32_t ob[8][2];
            const uint32_t oa = sb + SM_O + (lane & 7) * RB + (lane >> 3) * 16;
#pragma unroll
            for (int i2 = 0; i2 < 4; i2++) ldsm_x4(ob[2 * i2][0], ob[2 * i2][1], ob[2 * i2 + 1][0], ob[2 * i2 + 1][1], oa + i2 * 64);
            float c0[3][4], c1[3][4];
#pragma unroll
            for (int q = 0; q < 3; q++)
#pragma unroll
                for (int e = 0; e < 4; e++) c0[q][e] = c1[q][e] = 0.f;
#pragma unroll
            for (int i = 0; i < 8; i += 2) {
                uint4 a = *reinterpret_cast<const uint4*>(smem + SM_WO + ((w + 8) * 8 + i) * 512 + lane * 16);
                uint4 a2 = *reinterpret_cast<const uint4*>(smem + SM_WO + ((w + 8) * 8 + i + 1) * 512 + lane * 16);
                mma16816(c0[0], wpre[i].x, wpre[i].y, wpre[i].z, wpre[i].w, ob[i][0], ob[i][1]);
                mma16816(c1[0], wpre[i + 1].x, wpre[i + 1].y, wpre[i + 1].z, wpre[i + 1].w, ob[i + 1][0], ob[i + 1][1]);
                mma16816(c0[1], a.x, a.y, a.z, a.w, ob[i][0], ob[i][1]);
                mma16816(c1[1], a2.x, a2.y, a2.z, a2.w, ob[i + 1][0], ob[i + 1][1]);
            }
            if (three) {
#pragma unroll
                for (int i = 0; i < 8; i += 2) {
                    uint4 a = *reinterpret_cast<const uint4*>(smem + SM_WO + ((w + 16) * 8 + i) * 512 + lane * 16);
                    uint4 a2 = *reinterpret_cast<const uint4*>(smem + SM_WO + ((w + 16) * 8 + i + 1) * 512 + lane * 16);
                    mma16816(c0[2], a.x, a.y, a.z, a.w, ob[i][0], ob[i][1]);
                    mma16816(c1[2], a2.x, a2.y, a2.z, a2.w, ob[i + 1][0], ob[i + 1][1]);
                }
            }
            const bool odd = g & 1;
            float* dp = g_memacc + (size_t)(s + 1) * MT_ * D_ + (tile0 + w) * 128 + (2 * j + (odd ? 1 : 0)) * 16 + 4 * (g >> 1);
#pragma unroll
            for (int q = 0; q < 3; q++) {
#pragma unroll
                for (int e = 0; e < 4; e++) c0[q][e] += c1[q][e];
                float r1 = __shfl_xor_sync(0xffffffffu, odd ? c0[q][0] : c0[q][1], 4);
                float r2 = __shfl_xor_sync(0xffffffffu, odd ? c0[q][2] : c0[q][3], 4);
                float v0 = odd ? r1 : c0[q][0], v1 = odd ? c0[q][1] : r1, v2 = odd ? r2 : c0[q][2], v3 = odd ? c0[q][3] : r2;
                if (q < 2 || three)
                    asm volatile("red.global.add.v4.f32 [%0], {%1,%2,%3,%4};" ::"l"(dp + q * 1024), "f"(v0), "f"(v1), "f"(v2), "f"(v3)
                                 : "memory");
            }
        }
        __syncthreads();
        if (tid == 0) {
            asm volatile("fence.acq_rel.gpu;" ::: "memory");
            asm volatile("red.relaxed.gpu.global.add.u32 [%0], 1;" ::"l"(g_cnt + ((s + 1) * 3 + rank) * 32) : "memory");
            if (rank != 0) asm volatile("red.relaxed.gpu.global.add.u32 [%0], 1;" ::"l"(g_prog + s * 32) : "memory");
        }
        prefetch_kv(s + 1);
    }
    __syncthreads();
    if (tid == 0 && rank != 0) {
        __threadfence();
        asm volatile("red.relaxed.gpu.global.add.u32 [%0], 1;" ::"l"(g_prog + (NSEG_ - 1) * 32) : "memory");
    }
    cluster_arrive();
    cluster_wait();
}

__global__ void gate_kernel(int seg) {
    int guard = 0;
    const unsigned* p = seg < 0 ? &g_resident[0] : g_prog + seg * 32;
    const unsigned target = seg < 0 ? 96u : 64u;
    while (ld_acquire(p) < target && ++guard < (1 << 22)) __nanosleep(200);
}

constexpr int AT_PAIR = (32 + 40 + 48) * RB;
__global__ void __launch_bounds__(128) attn_kernel(int seg0) {
    extern __shared__ __align__(1024) uint8_t smem[];
    const int tid = threadIdx.x, w = tid >> 5, lane = tid & 31, g = lane >> 2, j = lane & 3;
    const int pair = w >> 1, half = w & 1;
    const int unit = seg0 * 32 + blockIdx.x * 2 + pair;
    const int s = unit >> 5, h = unit & 31;
    if (tid == 0) {
        int guard = 0;
        while (ld_acquire(g_prog + s * 32) < 64u && ++guard < (1 << 22)) __nanosleep(400);
    }
    __syncthreads();
    uint8_t* base = smem + pair * AT_PAIR;
    const uint32_t sQ = smem_u32(base), sK = sQ + 32 * RB, sV = sK + 40 * RB;
    const int t64 = tid & 63;
    for (int idx = t64; idx < 112 * 16; idx += 64) {
        int r = idx >> 4, ch = idx & 15;
        const bf16* src;
        uint32_t dst;
        if (r < 32) {
            src = g_q + (size_t)(s * SEG_ + r) * HD_; dst = sQ + r * RB;
        } else if (r < 40) {
            src = g_km + (size_t)(s * MT_ + r - 32) * HD_; dst = sK + (r - 32) * RB;
        } else if (r < 72) {
            src = g_k + (size_t)(s * SEG_ + r - 40) * HD_; dst = sK + (r - 32) * RB;
        } else if (r < 80) {
            src = g_vm + (size_t)(s * MT_ + r - 72) * HD_; dst = sV + (r - 72) * RB;
        } else {
            src = g_v + (size_t)(s * SEG_ + r - 80) * HD_; dst = sV + (r - 72) * RB;
        }
        cp_async16(dst + ch * 16, src + h * DH_ + ch * 8);
    }
    cp_async_commit();
    for (int i = t64; i < 8 * RB / 4; i += 64) *reinterpret_cast<uint32_t*>(base + (32 + 40 + 40) * RB + i * 4) = 0u;
    cp_async_wait_all();
    __syncthreads();

    const float scale = 0.08838834764831845f;
    float sc[5][4];
#pragma unroll
    for (int t = 0; t < 5; t++) sc[t][0] = sc[t][1] = sc[t][2] = sc[t][3] = 0.f;
    const uint32_t qa = sQ + (16 * half + (lane & 15)) * RB + (lane >> 4) * 16;
    const uint32_t ka = sK + (lane & 7) * RB + (lane >> 3) * 16;
#pragma unroll
    for (int i2 = 0; i2 < 4; i2++) {
        uint32_t a[2][4];
        ldsm_x4(a[0][0], a[0][1], a[0][2], a[0][3], qa + i2 * 64);
        ldsm_x4(a[1][0], a[1][1], a[1][2], a[1][3], qa + i2 * 64 + 32);
#pragma unroll
        for (int t = 0; t < 5; t++) {
            uint32_t b0, b1, b2, b3;
            ldsm_x4(b0, b1, b2, b3, ka + t * 8 * RB + i2 * 64);
            mma16816(sc[t], a[0][0], a[0][1], a[0][2], a[0][3], b0, b1);
            mma16816(sc[t], a[1][0], a[1][1], a[1][2], a[1][3], b2, b3);
        }
    }
    const int r0 = 16 * half + g, r1 = r0 + 8;
    float m0 = -INFINITY, m1 = -INFINITY;
#pragma unroll
    for (int t = 0; t < 5; t++) {
#pragma unroll
        for (int e = 0; e < 2; e++) {
            const int kx = 8 * (t - 1) + 2 * j + e;
            float a = bf16r(bf16r(sc[t][e]) * scale), b = bf16r(bf16r(sc[t][2 + e]) * scale);
            if (t > 0 && kx > r0) a = -1e9f;
            if (t > 0 && kx > r1) b = -1e9f;
            sc[t][e] = a; sc[t][2 + e] = b;
            m0 = fmaxf(m0, a); m1 = fmaxf(m1, b);
        }
    }
    m0 = fmaxf(m0, __shfl_xor_sync(0xffffffffu, m0, 1)); m0 = fmaxf(m0, __shfl_xor_sync(0xffffffffu, m0, 2));
    m1 = fmaxf(m1, __shfl_xor_sync(0xffffffffu, m1, 1)); m1 = fmaxf(m1, __shfl_xor_sync(0xffffffffu, m1, 2));
    float l0 = 0.f, l1 = 0.f;
#pragma unroll
    for (int t = 0; t < 5; t++) {
#pragma unroll
        for (int e = 0; e < 2; e++) {
            sc[t][e] = __expf(sc[t][e] - m0); sc[t][2 + e] = __expf(sc[t][2 + e] - m1);
            l0 += sc[t][e]; l1 += sc[t][2 + e];
        }
    }
    l0 += __shfl_xor_sync(0xffffffffu, l0, 1); l0 += __shfl_xor_sync(0xffffffffu, l0, 2);
    l1 += __shfl_xor_sync(0xffffffffu, l1, 1); l1 += __shfl_xor_sync(0xffffffffu, l1, 2);
    const float i0 = 1.0f / l0, i1 = 1.0f / l1;
    uint32_t plo[5], phi[5];
#pragma unroll
    for (int t = 0; t < 5; t++) {
        plo[t] = pack_bf16(sc[t][0] * i0, sc[t][1] * i0);
        phi[t] = pack_bf16(sc[t][2] * i1, sc[t][3] * i1);
    }
    const uint32_t va = sV + (lane & 15) * RB + (lane >> 4) * 16;
    bf16* orow0 = g_o + (size_t)(s * SEG_ + r0) * HD_ + h * DH_ + 2 * j;
    bf16* orow1 = g_o + (size_t)(s * SEG_ + r1) * HD_ + h * DH_ + 2 * j;
#pragma unroll
    for (int n2 = 0; n2 < 8; n2++) {
        float o0[4] = {0.f, 0.f, 0.f, 0.f}, o1[4] = {0.f, 0.f, 0.f, 0.f};
#pragma unroll
        for (int i = 0; i < 3; i++) {
            uint32_t b00, b01, b10, b11;
            ldsm_x4_t(b00, b01, b10, b11, va + i * 16 * RB + n2 * 32);
            const uint32_t a0 = plo[2 * i], a1 = phi[2 * i];
            const uint32_t a2 = (i < 2) ? plo[i < 2 ? 2 * i + 1 : 0] : 0u, a3 = (i < 2) ? phi[i < 2 ? 2 * i + 1 : 0] : 0u;
            mma16816(o0, a0, a1, a2, a3, b00, b01);
            mma16816(o1, a0, a1, a2, a3, b10, b11);
        }
        *reinterpret_cast<uint32_t*>(orow0 + n2 * 16) = pack_bf16(o0[0], o0[1]);
        *reinterpret_cast<uint32_t*>(orow1 + n2 * 16) = pack_bf16(o0[2], o0[3]);
        *reinterpret_cast<uint32_t*>(orow0 + n2 * 16 + 8) = pack_bf16(o1[0], o1[1]);
        *reinterpret_cast<uint32_t*>(orow1 + n2 * 16 + 8) = pack_bf16(o1[2], o1[3]);
    }
}

typedef CUresult (*EncodeFn)(CUtensorMap*, CUtensorMapDataType, cuuint32_t, void*, const cuuint64_t*, const cuuint64_t*,
                             const cuuint32_t*, const cuuint32_t*, CUtensorMapInterleave, CUtensorMapSwizzle,
                             CUtensorMapL2promotion, CUtensorMapFloatOOBfill);

void make_map(EncodeFn fn, CUtensorMap* m, const void* ptr, uint64_t rows, uint64_t cols, uint32_t box_cols, uint32_t box_rows) {
    cuuint64_t dims[2] = {cols, rows};
    cuuint64_t strides[1] = {cols * 2};
    cuuint32_t box[2] = {box_cols, box_rows};
    cuuint32_t es[2] = {1, 1};
    fn(m, CU_TENSOR_MAP_DATA_TYPE_BFLOAT16, 2, const_cast<void*>(ptr), dims, strides, box, es, CU_TENSOR_MAP_INTERLEAVE_NONE,
       CU_TENSOR_MAP_SWIZZLE_128B, CU_TENSOR_MAP_L2_PROMOTION_L2_256B, CU_TENSOR_MAP_FLOAT_OOB_FILL_NONE);
}

struct HostState {
    bool init;
    const void* ptrs[4];
    CUtensorMap tmXn, tmWq, tmWk, tmWv, tmO, tmWo;
    EncodeFn fn;
    cudaStream_t side, side2;
    cudaEvent_t evFork, evJoin, evFfn, evQ, evJoin2;
};
HostState g_host;

}

extern "C" void kernel_launch(void* const* d_in, const int* in_sizes, int n_in, void* d_out, int out_size) {
    const bf16* A_x = (const bf16*)d_in[0];
    const bf16* A_mem0 = (const bf16*)d_in[1];
    const bf16* A_Wq = (const bf16*)d_in[2];
    const bf16* A_Wk = (const bf16*)d_in[3];
    const bf16* A_Wv = (const bf16*)d_in[4];
    const bf16* A_Wo = (const bf16*)d_in[5];
    const bf16* B_wr = (const bf16*)d_in[8];
    const bf16* B_wg = (const bf16*)d_in[9];
    const bf16* B_wu = (const bf16*)d_in[10];
    const bf16* B_wd = (const bf16*)d_in[11];
    bf16* out = (bf16*)d_out;

    constexpr int QKV_BN = 256, QKV_ST = 4, OUT_BN = 128, OUT_ST = 6;
    auto* qkv_fn = gemm_kernel<QKV_BN, QKV_ST, D_ / 64, 0>;
    auto* out_fn = gemm_kernel<OUT_BN, OUT_ST, HD_ / 64, 1>;
    auto* outsk_fn = gemm_kernel<OUT_BN, OUT_ST, HD_ / 64 / 4, 2>;

    HostState& hs = g_host;
    if (!hs.init) {
        void* fp = nullptr;
        cudaDriverEntryPointQueryResult qr;
        cudaGetDriverEntryPoint("cuTensorMapEncodeTiled", &fp, cudaEnableDefault, &qr);
        hs.fn = (EncodeFn)fp;
        cudaFuncSetAttribute(qkv_fn, cudaFuncAttributeMaxDynamicSharedMemorySize, GemmSmem<QKV_BN, QKV_ST>::TOTAL);
        cudaFuncSetAttribute(out_fn, cudaFuncAttributeMaxDynamicSharedMemorySize, GemmSmem<OUT_BN, OUT_ST>::TOTAL);
        cudaFuncSetAttribute(outsk_fn, cudaFuncAttributeMaxDynamicSharedMemorySize, GemmSmem<OUT_BN, OUT_ST>::TOTAL);
        cudaFuncSetAttribute(rec_kernel, cudaFuncAttributeMaxDynamicSharedMemorySize, SM_TOTAL);
        cudaFuncSetAttribute(attn_kernel, cudaFuncAttributeMaxDynamicSharedMemorySize, 2 * AT_PAIR);
        void *pxn, *po;
        cudaGetSymbolAddress(&pxn, g_xn);
        cudaGetSymbolAddress(&po, g_o);
        make_map(hs.fn, &hs.tmXn, pxn, S_, D_, 64, 128);
        make_map(hs.fn, &hs.tmO, po, S_, HD_, 64, 128);
        cudaStreamCreateWithFlags(&hs.side, cudaStreamNonBlocking);
        cudaStreamCreateWithFlags(&hs.side2, cudaStreamNonBlocking);
        cudaEventCreateWithFlags(&hs.evFfn, cudaEventDisableTiming);
        cudaEventCreateWithFlags(&hs.evQ, cudaEventDisableTiming);
        cudaEventCreateWithFlags(&hs.evJoin2, cudaEventDisableTiming);
        cudaEventCreateWithFlags(&hs.evFork, cudaEventDisableTiming);
        cudaEventCreateWithFlags(&hs.evJoin, cudaEventDisableTiming);
        hs.init = true;
    }
    if (hs.ptrs[0] != A_Wq || hs.ptrs[1] != A_Wk || hs.ptrs[2] != A_Wv || hs.ptrs[3] != A_Wo) {
        make_map(hs.fn, &hs.tmWq, A_Wq, D_, HD_, 64, 64);
        make_map(hs.fn, &hs.tmWk, A_Wk, D_, HD_, 64, 64);
        make_map(hs.fn, &hs.tmWv, A_Wv, D_, HD_, 64, 64);
        make_map(hs.fn, &hs.tmWo, A_Wo, HD_, D_, 64, 64);
        hs.ptrs[0] = A_Wq; hs.ptrs[1] = A_Wk; hs.ptrs[2] = A_Wv; hs.ptrs[3] = A_Wo;
    }

    constexpr int QKV_SM = GemmSmem<QKV_BN, QKV_ST>::TOTAL, OUT_SM = GemmSmem<OUT_BN, OUT_ST>::TOTAL;
    constexpr int NT = HD_ / QKV_BN;
    cudaStream_t mainS = cudaStreamPerThread, side = hs.side;
    ln_kernel<<<256, 256, 0, mainS>>>(A_x, B_wr, A_mem0);
    cudaEventRecord(hs.evFork, mainS);
    cudaStreamWaitEvent(side, hs.evFork, 0);
    cudaStreamWaitEvent(hs.side2, hs.evFork, 0);
    qkv_fn<<<dim3(16, 2 * NT), 384, QKV_SM, mainS>>>(hs.tmXn, hs.tmWq, hs.tmWk, hs.tmWv, nullptr, nullptr, NT, 0);
    rec_kernel<<<96, 256, SM_TOTAL, mainS>>>(A_Wq, A_Wk, A_Wv, A_Wo);
    ffn1_kernel<<<112, 256, 0, hs.side2>>>(B_wg, B_wu);
    ffn2_kernel<<<64, 256, 0, hs.side2>>>(B_wd);
    cudaEventRecord(hs.evFfn, hs.side2);
    gate_kernel<<<1, 1, 0, side>>>(-1);
    qkv_fn<<<dim3(16, NT), 384, QKV_SM, side>>>(hs.tmXn, hs.tmWq, hs.tmWk, hs.tmWv, nullptr, nullptr, 0, 0);
    cudaEventRecord(hs.evQ, side);
    {
        const int chunk_mt[4] = {4, 4, 3, 3};
        int mt0 = 0;
        for (int c = 0; c < 4; c++) {
            attn_kernel<<<chunk_mt[c] * 4 * H_ / 2, 128, 2 * AT_PAIR, side>>>(mt0 * 4);
            if (c == 0) cudaStreamWaitEvent(side, hs.evFfn, 0);
            out_fn<<<dim3(chunk_mt[c], D_ / OUT_BN), 384, OUT_SM, side>>>(hs.tmO, hs.tmWo, hs.tmWo, hs.tmWo, A_x, out, 0, mt0);
            mt0 += chunk_mt[c];
        }
    }
    cudaStreamWaitEvent(hs.side2, hs.evQ, 0);
    gate_kernel<<<1, 1, 0, hs.side2>>>(NSEG_ - 4);
    attn_kernel<<<8 * H_ / 2, 128, 2 * AT_PAIR, hs.side2>>>(NSEG_ - 8);
    outsk_fn<<<dim3(2, D_ / OUT_BN, 4), 384, OUT_SM, hs.side2>>>(hs.tmO, hs.tmWo, hs.tmWo, hs.tmWo, A_x, out, 0, 14);
    fin_kernel<<<256, 128, 0, hs.side2>>>(A_x, out, S_ - 256);
    cudaEventRecord(hs.evJoin, side);
    cudaEventRecord(hs.evJoin2, hs.side2);
    cudaStreamWaitEvent(mainS, hs.evJoin, 0);
    cudaStreamWaitEvent(mainS, hs.evJoin2, 0);
}
```

```cpp
#include <cuda_runtime.h>
#include <cuda_bf16.h>
#include <cuda.h>
#include <stdint.h>

typedef __nv_bfloat16 bf16;

namespace {

constexpr int S_ = 2048, D_ = 1024, H_ = 32, DH_ = 128, HD_ = 4096, MT_ = 8, SEG_ = 32, NSEG_ = 64, F_ = 3584;

__device__ __align__(1024) bf16 g_xn[S_ * D_];
__device__ __align__(1024) bf16 g_q[S_ * HD_];
__device__ __align__(1024) bf16 g_k[S_ * HD_];
__device__ __align__(1024) bf16 g_v[S_ * HD_];
__device__ __align__(1024) bf16 g_o[S_ * HD_];
__device__ __align__(1024) float g_memacc[NSEG_ * MT_ * D_];
__device__ __align__(1024) unsigned g_cnt[NSEG_ * 3 * 32];
__device__ __align__(128) unsigned g_resident[32];
__device__ __align__(1024) unsigned g_prog[NSEG_ * 32];
__device__ __align__(1024) bf16 g_km[NSEG_ * MT_ * HD_];
__device__ __align__(1024) bf16 g_vm[NSEG_ * MT_ * HD_];
__device__ __align__(1024) float g_part[256 * D_];
__device__ float g_r[S_];
__device__ float g_h[2 * F_];
__device__ float g_upd[2 * D_];
__device__ int g_idx[2];

__device__ __forceinline__ float bf16r(float x) { return __bfloat162float(__float2bfloat16_rn(x)); }
__device__ __forceinline__ uint32_t pack_bf16(float lo, float hi) {
    __nv_bfloat162 t = __floats2bfloat162_rn(lo, hi);
    return *reinterpret_cast<uint32_t*>(&t);
}
__device__ __forceinline__ float bf_lo(uint32_t u) { return __uint_as_float(u << 16); }
__device__ __forceinline__ float bf_hi(uint32_t u) { return __uint_as_float(u & 0xffff0000u); }
__device__ __forceinline__ uint32_t smem_u32(const void* p) { return (uint32_t)__cvta_generic_to_shared(p); }

__device__ __forceinline__ void mbar_init(uint32_t a, uint32_t cnt) {
    asm volatile("mbarrier.init.shared::cta.b64 [%0], %1;" ::"r"(a), "r"(cnt) : "memory");
}
__device__ __forceinline__ void mbar_expect_tx(uint32_t a, uint32_t bytes) {
    asm volatile("mbarrier.arrive.expect_tx.shared::cta.b64 _, [%0], %1;" ::"r"(a), "r"(bytes) : "memory");
}
__device__ __forceinline__ void mbar_wait(uint32_t a, uint32_t parity) {
    asm volatile(
        "{\n"
        ".reg .pred p;\n"
        "WAIT_%=:\n"
        "mbarrier.try_wait.parity.shared::cta.b64 p, [%0], %1;\n"
        "@p bra DONE_%=;\n"
        "bra WAIT_%=;\n"
        "DONE_%=:\n"
        "}\n" ::"r"(a), "r"(parity) : "memory");
}
__device__ __forceinline__ uint32_t mapa(uint32_t a, uint32_t rank) {
    uint32_t r;
    asm volatile("mapa.shared::cluster.u32 %0, %1, %2;" : "=r"(r) : "r"(a), "r"(rank));
    return r;
}
__device__ __forceinline__ void cluster_arrive() { asm volatile("barrier.cluster.arrive.release.aligned;" ::: "memory"); }
__device__ __forceinline__ void cluster_wait() { asm volatile("barrier.cluster.wait.acquire.aligned;" ::: "memory"); }
__device__ __forceinline__ uint32_t cluster_ctarank() {
    uint32_t r;
    asm volatile("mov.u32 %0, %%cluster_ctarank;" : "=r"(r));
    return r;
}
__device__ __forceinline__ void tma_load_2d(uint32_t dst, const CUtensorMap* map, uint32_t bar, int c0, int c1) {
    asm volatile(
        "cp.async.bulk.tensor.2d.shared::cluster.global.mbarrier::complete_tx::bytes [%0], [%1, {%3, %4}], [%2];" ::"r"(dst),
        "l"(map), "r"(bar), "r"(c0), "r"(c1)
        : "memory");
}
__device__ __forceinline__ void mma16816(float (&d)[4], uint32_t a0, uint32_t a1, uint32_t a2, uint32_t a3, uint32_t b0,
                                         uint32_t b1) {
    asm volatile(
        "mma.sync.aligned.m16n8k16.row.col.f32.bf16.bf16.f32 {%0,%1,%2,%3}, {%4,%5,%6,%7}, {%8,%9}, {%0,%1,%2,%3};"
        : "+f"(d[0]), "+f"(d[1]), "+f"(d[2]), "+f"(d[3])
        : "r"(a0), "r"(a1), "r"(a2), "r"(a3), "r"(b0), "r"(b1));
}
__device__ __forceinline__ void ldsm_x4(uint32_t& r0, uint32_t& r1, uint32_t& r2, uint32_t& r3, uint32_t a) {
    asm volatile("ldmatrix.sync.aligned.m8n8.x4.shared.b16 {%0,%1,%2,%3}, [%4];"
                 : "=r"(r0), "=r"(r1), "=r"(r2), "=r"(r3)
                 : "r"(a)
                 : "memory");
}
__device__ __forceinline__ void ldsm_x4_t(uint32_t& r0, uint32_t& r1, uint32_t& r2, uint32_t& r3, uint32_t a) {
    asm volatile("ldmatrix.sync.aligned.m8n8.x4.trans.shared.b16 {%0,%1,%2,%3}, [%4];"
                 : "=r"(r0), "=r"(r1), "=r"(r2), "=r"(r3)
                 : "r"(a)
                 : "memory");
}
__device__ __forceinline__ uint32_t movm_t(uint32_t a) {
    uint32_t d;
    asm volatile("movmatrix.sync.aligned.m8n8.trans.b16 %0, %1;" : "=r"(d) : "r"(a));
    return d;
}
__device__ __forceinline__ void cp_async16(uint32_t dst, const void* src) {
    asm volatile("cp.async.cg.shared.global [%0], [%1], 16;" ::"r"(dst), "l"(src) : "memory");
}
__device__ __forceinline__ void cp_async_commit() { asm volatile("cp.async.commit_group;" ::: "memory"); }
__device__ __forceinline__ void cp_async_wait_all() { asm volatile("cp.async.wait_all;" ::: "memory"); }

__global__ void __launch_bounds__(256) ln_kernel(const bf16* __restrict__ x, const bf16* __restrict__ w_r,
                                                 const bf16* __restrict__ mem0) {
    const int warp = threadIdx.x >> 5, lane = threadIdx.x & 31;
    const int row = blockIdx.x * 8 + warp;
    const uint4* xp = reinterpret_cast<const uint4*>(x + (size_t)row * D_);
    const uint4* wp = reinterpret_cast<const uint4*>(w_r);
    float v[32];
    float sum = 0.f;
#pragma unroll
    for (int c = 0; c < 4; c++) {
        uint4 u = xp[c * 32 + lane];
        uint32_t w[4] = {u.x, u.y, u.z, u.w};
#pragma unroll
        for (int i = 0; i < 4; i++) {
            v[c * 8 + 2 * i] = bf_lo(w[i]);
            v[c * 8 + 2 * i + 1] = bf_hi(w[i]);
            sum += v[c * 8 + 2 * i] + v[c * 8 + 2 * i + 1];
        }
    }
#pragma unroll
    for (int o = 16; o; o >>= 1) sum += __shfl_xor_sync(0xffffffffu, sum, o);
    const float mean = sum * (1.0f / D_);
    float sq = 0.f;
#pragma unroll
    for (int i = 0; i < 32; i++) {
        float d = v[i] - mean;
        sq += d * d;
    }
#pragma unroll
    for (int o = 16; o; o >>= 1) sq += __shfl_xor_sync(0xffffffffu, sq, o);
    const float mb = bf16r(mean);
    const float vb = bf16r(sq * (1.0f / D_));
    const float den = bf16r(sqrtf(bf16r(vb + 1e-5f)));
    float racc = 0.f;
    uint4* op = reinterpret_cast<uint4*>(g_xn + (size_t)row * D_);
#pragma unroll
    for (int c = 0; c < 4; c++) {
        uint4 wu = wp[c * 32 + lane];
        uint32_t ww[4] = {wu.x, wu.y, wu.z, wu.w};
        uint32_t o[4];
#pragma unroll
        for (int i = 0; i < 4; i++) {
            float a = bf16r(__fdiv_rn(bf16r(v[c * 8 + 2 * i] - mb), den));
            float b = bf16r(__fdiv_rn(bf16r(v[c * 8 + 2 * i + 1] - mb), den));
            racc += a * bf_lo(ww[i]) + b * bf_hi(ww[i]);
            o[i] = pack_bf16(a, b);
        }
        op[c * 32 + lane] = make_uint4(o[0], o[1], o[2], o[3]);
    }
#pragma unroll
    for (int o = 16; o; o >>= 1) racc += __shfl_xor_sync(0xffffffffu, racc, o);
    if (lane == 0) g_r[row] = bf16r(racc);

    {
        const int per = NSEG_ * MT_ * D_ / 256;
        float4* mp = reinterpret_cast<float4*>(g_memacc + (size_t)blockIdx.x * per);
        for (int i = threadIdx.x; i < per / 4; i += 256) {
            int e = blockIdx.x * per + i * 4;
            float4 z = make_float4(0.f, 0.f, 0.f, 0.f);
            if (e < MT_ * D_) {
                const int src = ((e >> 4) & 7) * D_ + (e >> 7) * 16 + (e & 15);
                z.x = __bfloat162float(mem0[src]);
                z.y = __bfloat162float(mem0[src + 1]);
                z.z = __bfloat162float(mem0[src + 2]);
                z.w = __bfloat162float(mem0[src + 3]);
            }
            mp[i] = z;
        }
        if (threadIdx.x < NSEG_ * 3 * 32 / 256) g_cnt[blockIdx.x * (NSEG_ * 3 * 32 / 256) + threadIdx.x] = 0u;
        if (threadIdx.x < NSEG_ * 32 / 256) g_prog[blockIdx.x * (NSEG_ * 32 / 256) + threadIdx.x] = 0u;
        if (blockIdx.x == 0 && threadIdx.x == 0) g_resident[0] = 0u;
        reinterpret_cast<float4*>(g_part)[blockIdx.x * 256 + threadIdx.x] = make_float4(0.f, 0.f, 0.f, 0.f);
    }
}

__device__ __forceinline__ void top2_block(int& i0, int& i1, float* sv, int* si) {
    const int tid = threadIdx.x;
    float b0 = -INFINITY, b1 = -INFINITY;
    int j0 = 0x7fffffff, j1 = 0x7fffffff;
    for (int t = tid; t < S_; t += 256) {
        float v = g_r[t];
        if (v > b0 || (v == b0 && t < j0)) {
            b1 = b0; j1 = j0; b0 = v; j0 = t;
        } else if (v > b1 || (v == b1 && t < j1)) {
            b1 = v; j1 = t;
        }
    }
    sv[tid * 2] = b0; si[tid * 2] = j0; sv[tid * 2 + 1] = b1; si[tid * 2 + 1] = j1;
    __syncthreads();
    if (tid < 32) {
        float c0 = -INFINITY, c1 = -INFINITY;
        int k0 = 0x7fffffff, k1 = 0x7fffffff;
        for (int t = tid; t < 512; t += 32) {
            float v = sv[t]; int id = si[t];
            if (v > c0 || (v == c0 && id < k0)) {
                c1 = c0; k1 = k0; c0 = v; k0 = id;
            } else if (v > c1 || (v == c1 && id < k1)) {
                c1 = v; k1 = id;
            }
        }
#pragma unroll
        for (int o = 16; o; o >>= 1) {
            float d0 = __shfl_xor_sync(0xffffffffu, c0, o), d1 = __shfl_xor_sync(0xffffffffu, c1, o);
            int e0 = __shfl_xor_sync(0xffffffffu, k0, o), e1 = __shfl_xor_sync(0xffffffffu, k1, o);
            bool dfirst = (d0 > c0) || (d0 == c0 && e0 < k0);
            float n0 = dfirst ? d0 : c0; int m0 = dfirst ? e0 : k0;
            float a = dfirst ? c0 : d0; int ai = dfirst ? k0 : e0;
            float b = dfirst ? d1 : c1; int bi = dfirst ? e1 : k1;
            bool afirst = (a > b) || (a == b && ai < bi);
            c0 = n0; k0 = m0; c1 = afirst ? a : b; k1 = afirst ? ai : bi;
        }
        if (tid == 0) { si[0] = k0; si[1] = k1; }
    }
    __syncthreads();
    i0 = si[0]; i1 = si[1];
    __syncthreads();
}

__global__ void __launch_bounds__(256) ffn1_kernel(const bf16* __restrict__ wg, const bf16* __restrict__ wu) {
    __shared__ float sv[512];
    __shared__ int si[512];
    __shared__ float sx[2][D_];
    __shared__ float red[64][4][33];
    int i0, i1;
    top2_block(i0, i1, sv, si);
    const int tid = threadIdx.x;
    if (blockIdx.x == 0 && tid == 0) { g_idx[0] = i0; g_idx[1] = i1; }
    for (int t = tid; t < D_; t += 256) {
        sx[0][t] = __bfloat162float(g_xn[(size_t)i0 * D_ + t]);
        sx[1][t] = __bfloat162float(g_xn[(size_t)i1 * D_ + t]);
    }
    __syncthreads();
    const int cq = tid & 3, rg = tid >> 2;
    const int col0 = blockIdx.x * 32 + cq * 8;
    float acc[4][8];
#pragma unroll
    for (int a = 0; a < 4; a++)
#pragma unroll
        for (int b = 0; b < 8; b++) acc[a][b] = 0.f;
#pragma unroll 4
    for (int p = 0; p < 16; p++) {
        int d = p * 64 + rg;
        uint4 ug = __ldg(reinterpret_cast<const uint4*>(wg + (size_t)d * F_ + col0));
        uint4 uu = __ldg(reinterpret_cast<const uint4*>(wu + (size_t)d * F_ + col0));
        float x0 = sx[0][d], x1 = sx[1][d];
        uint32_t a[4] = {ug.x, ug.y, ug.z, ug.w}, b[4] = {uu.x, uu.y, uu.z, uu.w};
#pragma unroll
        for (int i = 0; i < 4; i++) {
            acc[0][2 * i] += x0 * bf_lo(a[i]); acc[0][2 * i + 1] += x0 * bf_hi(a[i]);
            acc[1][2 * i] += x1 * bf_lo(a[i]); acc[1][2 * i + 1] += x1 * bf_hi(a[i]);
            acc[2][2 * i] += x0 * bf_lo(b[i]); acc[2][2 * i + 1] += x0 * bf_hi(b[i]);
            acc[3][2 * i] += x1 * bf_lo(b[i]); acc[3][2 * i + 1] += x1 * bf_hi(b[i]);
        }
    }
#pragma unroll
    for (int a = 0; a < 4; a++)
#pragma unroll
        for (int b = 0; b < 8; b++) red[rg][a][cq * 8 + b] = acc[a][b];
    __syncthreads();
    if (tid < 128) {
        int a = tid >> 5, c = tid & 31;
        float s = 0.f;
        for (int r = 0; r < 64; r++) s += red[r][a][c];
        red[0][a][c] = bf16r(s);
    }
    __syncthreads();
    if (tid < 64) {
        int tk = tid >> 5, c = tid & 31;
        float g = red[0][tk][c], u = red[0][2 + tk][c];
        float sg = bf16r(g / (1.0f + __expf(-g)));
        g_h[tk * F_ + blockIdx.x * 32 + c] = bf16r(sg * u);
    }
}

__global__ void __launch_bounds__(256) ffn2_kernel(const bf16* __restrict__ wd) {
    __shared__ float sh[2][F_];
    __shared__ float red[128][2][17];
    const int tid = threadIdx.x;
    for (int t = tid; t < 2 * F_; t += 256) (&sh[0][0])[t] = g_h[t];
    __syncthreads();
    const int ch = tid & 1, rg = tid >> 1;
    const int col0 = blockIdx.x * 16 + ch * 8;
    float acc[2][8];
#pragma unroll
    for (int b = 0; b < 8; b++) acc[0][b] = acc[1][b] = 0.f;
#pragma unroll 7
    for (int p = 0; p < 28; p++) {
        int f = p * 128 + rg;
        uint4 u = __ldg(reinterpret_cast<const uint4*>(wd + (size_t)f * D_ + col0));
        float h0 = sh[0][f], h1 = sh[1][f];
        uint32_t a[4] = {u.x, u.y, u.z, u.w};
#pragma unroll
        for (int i = 0; i < 4; i++) {
            acc[0][2 * i] += h0 * bf_lo(a[i]); acc[0][2 * i + 1] += h0 * bf_hi(a[i]);
            acc[1][2 * i] += h1 * bf_lo(a[i]); acc[1][2 * i + 1] += h1 * bf_hi(a[i]);
        }
    }
#pragma unroll
    for (int b = 0; b < 8; b++) { red[rg][0][ch * 8 + b] = acc[0][b]; red[rg][1][ch * 8 + b] = acc[1][b]; }
    __syncthreads();
    if (tid < 32) {
        int tk = tid >> 4, c = tid & 15;
        float s = 0.f;
        for (int r = 0; r < 128; r++) s += red[r][tk][c];
        float y = bf16r(s);
        float rv = g_r[g_idx[tk]];
        float sg = bf16r(1.0f / (1.0f + __expf(-rv)));
        g_upd[tk * D_ + blockIdx.x * 16 + c] = bf16r(y * sg);
    }
}

__device__ __forceinline__ uint64_t make_desc(uint32_t addr, uint32_t lbo_bytes, uint32_t sbo_bytes) {
    return (uint64_t)((addr & 0x3FFFF) >> 4) | ((uint64_t)(lbo_bytes >> 4) << 16) | ((uint64_t)(sbo_bytes >> 4) << 32) |
           (1ull << 62);
}
__device__ __forceinline__ void wgmma_fence() { asm volatile("wgmma.fence.sync.aligned;" ::: "memory"); }
__device__ __forceinline__ void wgmma_commit() { asm volatile("wgmma.commit_group.sync.aligned;" ::: "memory"); }
template <int N>
__device__ __forceinline__ void wgmma_wait() { asm volatile("wgmma.wait_group.sync.aligned %0;" ::"n"(N) : "memory"); }

#define ACC8(b) "+f"(d[b]), "+f"(d[b + 1]), "+f"(d[b + 2]), "+f"(d[b + 3]), "+f"(d[b + 4]), "+f"(d[b + 5]), "+f"(d[b + 6]), "+f"(d[b + 7])
#define ACC32(b) ACC8(b), ACC8(b + 8), ACC8(b + 16), ACC8(b + 24)

__device__ __forceinline__ void wgmma_n128(float (&d)[64], uint64_t da, uint64_t db, int scale_d) {
    asm volatile(
        "{\n.reg .pred p;\nsetp.ne.b32 p, %66, 0;\n"
        "wgmma.mma_async.sync.aligned.m64n128k16.f32.bf16.bf16 "
        "{%0,%1,%2,%3,%4,%5,%6,%7,%8,%9,%10,%11,%12,%13,%14,%15,%16,%17,%18,%19,%20,%21,%22,%23,%24,%25,%26,%27,%28,%29,%30,%31,"
        "%32,%33,%34,%35,%36,%37,%38,%39,%40,%41,%42,%43,%44,%45,%46,%47,%48,%49,%50,%51,%52,%53,%54,%55,%56,%57,%58,%59,%60,%61,%62,%63},"
        " %64, %65, p, 1, 1, 0, 1;\n}\n"
        : ACC32(0), ACC32(32)
        : "l"(da), "l"(db), "r"(scale_d));
}
__device__ __forceinline__ void wgmma_n256(float (&d)[128], uint64_t da, uint64_t db, int scale_d) {
    asm volatile(
        "{\n.reg .pred p;\nsetp.ne.b32 p, %130, 0;\n"
        "wgmma.mma_async.sync.aligned.m64n256k16.f32.bf16.bf16 "
        "{%0,%1,%2,%3,%4,%5,%6,%7,%8,%9,%10,%11,%12,%13,%14,%15,%16,%17,%18,%19,%20,%21,%22,%23,%24,%25,%26,%27,%28,%29,%30,%31,"
        "%32,%33,%34,%35,%36,%37,%38,%39,%40,%41,%42,%43,%44,%45,%46,%47,%48,%49,%50,%51,%52,%53,%54,%55,%56,%57,%58,%59,%60,%61,%62,%63,"
        "%64,%65,%66,%67,%68,%69,%70,%71,%72,%73,%74,%75,%76,%77,%78,%79,%80,%81,%82,%83,%84,%85,%86,%87,%88,%89,%90,%91,%92,%93,%94,%95,"
        "%96,%97,%98,%99,%100,%101,%102,%103,%104,%105,%106,%107,%108,%109,%110,%111,%112,%113,%114,%115,%116,%117,%118,%119,%120,%121,%122,%123,%124,%125,%126,%127},"
        " %128, %129, p, 1, 1, 0, 1;\n}\n"
        : ACC32(0), ACC32(32), ACC32(64), ACC32(96)
        : "l"(da), "l"(db), "r"(scale_d));
}

template <int BN, int STAGES>
struct GemmSmem {
    static constexpr int A_BYTES = 128 * 64 * 2;
    static constexpr int B_BYTES = BN * 64 * 2;
    static constexpr int STAGE_BYTES = A_BYTES + B_BYTES;
    static constexpr int TOTAL = STAGES * STAGE_BYTES + 1024   + 256  ;
};

template <int BN, int STAGES, int KT, int EPI>
__global__ void __launch_bounds__(384, 1)
    gemm_kernel(const __grid_constant__ CUtensorMap tmA, const __grid_constant__ CUtensorMap tmB0,
                const __grid_constant__ CUtensorMap tmB1, const __grid_constant__ CUtensorMap tmB2,
                const bf16* __restrict__ xin, bf16* __restrict__ out, int n_tile_base, int m_tile_base) {
    using L = GemmSmem<BN, STAGES>;
    extern __shared__ uint8_t smem_raw[];
    const uint32_t sbase = (smem_u32(smem_raw) + 1023u) & ~1023u;
    const uint32_t bar_base = sbase + STAGES * L::STAGE_BYTES;
    auto full_bar = [&](int s) { return bar_base + s * 8; };
    auto empty_bar = [&](int s) { return bar_base + 64 + s * 8; };
    const int tid = threadIdx.x, wg = tid >> 7;
    const int m0 = (blockIdx.x + m_tile_base) * 128;
    const int ntile = blockIdx.y + n_tile_base;
    const int k0 = (EPI == 2) ? blockIdx.z * KT * 64 : 0;
    if (EPI == 0) asm volatile("griddepcontrol.launch_dependents;");

    if (tid == 0) {
        for (int s = 0; s < STAGES; s++) {
            mbar_init(full_bar(s), 1);
            mbar_init(empty_bar(s), 2);
        }
        asm volatile("fence.mbarrier_init.release.cluster;" ::: "memory");
    }
    __syncthreads();

    if (wg == 0) {
        asm volatile("setmaxnreg.dec.sync.aligned.u32 40;");
        if (tid == 0) {
            const CUtensorMap* tb;
            int n0;
            if (EPI == 0) {
                const int which = ntile / (HD_ / BN);
                tb = which == 0 ? &tmB0 : (which == 1 ? &tmB1 : &tmB2);
                n0 = (ntile % (HD_ / BN)) * BN;
            } else {
                tb = &tmB0;
                n0 = ntile * BN;
            }
            for (int kt = 0; kt < KT; kt++) {
                const int s = kt % STAGES;
                const uint32_t ph = (kt / STAGES) & 1;
                mbar_wait(empty_bar(s), ph ^ 1);
                mbar_expect_tx(full_bar(s), L::STAGE_BYTES);
                const uint32_t sa = sbase + s * L::STAGE_BYTES;
                tma_load_2d(sa, &tmA, full_bar(s), k0 + kt * 64, m0);
#pragma unroll
                for (int box = 0; box < BN / 64; box++)
                    tma_load_2d(sa + L::A_BYTES + box * 8192, tb, full_bar(s), n0 + box * 64, k0 + kt * 64);
            }
        }
    } else {
        asm volatile("setmaxnreg.inc.sync.aligned.u32 232;");
        const int cw = wg - 1;
        float acc[BN / 2];
        for (int kt = 0; kt < KT; kt++) {
            const int s = kt % STAGES;
            const uint32_t ph = (kt / STAGES) & 1;
            mbar_wait(full_bar(s), ph);
            const uint32_t sa = sbase + s * L::STAGE_BYTES + cw * 8192;
            const uint32_t sb = sbase + s * L::STAGE_BYTES + L::A_BYTES;
            wgmma_fence();
#pragma unroll
            for (int kk = 0; kk < 4; kk++) {
                uint64_t da = make_desc(sa + kk * 32, 16, 1024);
                uint64_t db = make_desc(sb + kk * 2048, 8192, 1024);
                if constexpr (BN == 256) wgmma_n256(acc, da, db, (kt | kk) != 0);
                else wgmma_n128(acc, da, db, (kt | kk) != 0);
            }
            wgmma_commit();
            if (kt > 0) {
                wgmma_wait<1>();
                if ((tid & 127) == 0) {
                    const int ps = (kt - 1) % STAGES;
                    asm volatile("mbarrier.arrive.shared::cta.b64 _, [%0];" ::"r"(empty_bar(ps)) : "memory");
                }
            }
        }
        wgmma_wait<0>();
        if constexpr (EPI == 2) {
            const int wq2 = (tid >> 5) & 3, l2 = tid & 31;
            float* pp = g_part + (size_t)(blockIdx.x * 128 + cw * 64 + wq2 * 16 + (l2 >> 2)) * D_ + ntile * BN + 2 * (l2 & 3);
#pragma unroll
            for (int c = 0; c < BN / 8; c++) {
                asm volatile("red.global.add.v2.f32 [%0], {%1,%2};" ::"l"(pp + c * 8), "f"(acc[c * 4]), "f"(acc[c * 4 + 1]) : "memory");
                asm volatile("red.global.add.v2.f32 [%0], {%1,%2};" ::"l"(pp + 8 * D_ + c * 8), "f"(acc[c * 4 + 2]), "f"(acc[c * 4 + 3]) : "memory");
            }
            return;
        }
        asm volatile("bar.sync 1, 256;" ::: "memory");
        constexpr int ROWB = BN * 2 + 16;
        const uint32_t stg = sbase + cw * (64 * ROWB);
        const int wq = (tid >> 5) & 3, lane = tid & 31, g = lane >> 2, j = lane & 3;
#pragma unroll
        for (int c = 0; c < BN / 8; c++) {
            uint32_t lo = pack_bf16(acc[c * 4], acc[c * 4 + 1]);
            uint32_t hi = pack_bf16(acc[c * 4 + 2], acc[c * 4 + 3]);
            uint32_t a0 = stg + (wq * 16 + g) * ROWB + c * 16 + j * 4;
            asm volatile("st.shared.b32 [%0], %1;" ::"r"(a0), "r"(lo) : "memory");
            asm volatile("st.shared.b32 [%0], %1;" ::"r"(a0 + 8 * ROWB), "r"(hi) : "memory");
        }
        __syncwarp();
        constexpr int CPR = BN / 8;
        if (EPI == 0) {
            const int which = ntile / (HD_ / BN);
            bf16* dst = which == 0 ? g_q : (which == 1 ? g_k : g_v);
            const int n0 = (ntile % (HD_ / BN)) * BN;
#pragma unroll
            for (int it = 0; it < 16 * CPR / 32; it++) {
                int idx = it * 32 + lane;
                int r = idx / CPR, ch = idx % CPR;
                uint4 v;
                asm volatile("ld.shared.v4.b32 {%0,%1,%2,%3}, [%4];"
                             : "=r"(v.x), "=r"(v.y), "=r"(v.z), "=r"(v.w)
                             : "r"(stg + (wq * 16 + r) * ROWB + ch * 16));
                int row = m0 + cw * 64 + wq * 16 + r;
                *reinterpret_cast<uint4*>(dst + (size_t)row * HD_ + n0 + ch * 8) = v;
            }
        } else {
            const int n0 = ntile * BN;
            const int i0 = g_idx[0], i1 = g_idx[1];
#pragma unroll
            for (int it = 0; it < 16 * CPR / 32; it++) {
                int idx = it * 32 + lane;
                int r = idx / CPR, ch = idx % CPR;
                uint4 v;
                asm volatile("ld.shared.v4.b32 {%0,%1,%2,%3}, [%4];"
                             : "=r"(v.x), "=r"(v.y), "=r"(v.z), "=r"(v.w)
                             : "r"(stg + (wq * 16 + r) * ROWB + ch * 16));
                int row = m0 + cw * 64 + wq * 16 + r;
                size_t off = (size_t)row * D_ + n0 + ch * 8;
                uint4 xv = __ldg(reinterpret_cast<const uint4*>(xin + off));
                uint4 nv = *reinterpret_cast<const uint4*>(g_xn + off);
                uint32_t av[4] = {v.x, v.y, v.z, v.w}, xa[4] = {xv.x, xv.y, xv.z, xv.w}, na[4] = {nv.x, nv.y, nv.z, nv.w};
                uint32_t ov[4];
                const float* up = (row == i0) ? (g_upd + n0 + ch * 8) : ((row == i1) ? (g_upd + D_ + n0 + ch * 8) : nullptr);
#pragma unroll
                for (int i = 0; i < 4; i++) {
                    float b0 = bf_lo(na[i]), b1 = bf_hi(na[i]);
                    if (up) { b0 = bf16r(b0 + up[2 * i]); b1 = bf16r(b1 + up[2 * i + 1]); }
                    float t0 = bf16r(bf_lo(xa[i]) + bf_lo(av[i])), t1 = bf16r(bf_hi(xa[i]) + bf_hi(av[i]));
                    ov[i] = pack_bf16(t0 + b0, t1 + b1);
                }
                *reinterpret_cast<uint4*>(out + off) = make_uint4(ov[0], ov[1], ov[2], ov[3]);
            }
        }
    }
}

__global__ void __launch_bounds__(128) fin_kernel(const bf16* __restrict__ xin, bf16* __restrict__ out, int row0) {
    const int row = row0 + blockIdx.x, c = threadIdx.x * 8;
    const size_t off = (size_t)row * D_ + c;
    const float4 a0 = __ldcg(reinterpret_cast<const float4*>(g_part + (size_t)blockIdx.x * D_ + c));
    const float4 a1 = __ldcg(reinterpret_cast<const float4*>(g_part + (size_t)blockIdx.x * D_ + c + 4));
    const float av[8] = {a0.x, a0.y, a0.z, a0.w, a1.x, a1.y, a1.z, a1.w};
    const uint4 xv = __ldg(reinterpret_cast<const uint4*>(xin + off));
    const uint4 nv = *reinterpret_cast<const uint4*>(g_xn + off);
    const uint32_t xa[4] = {xv.x, xv.y, xv.z, xv.w}, na[4] = {nv.x, nv.y, nv.z, nv.w};
    const float* up = (row == g_idx[0]) ? (g_upd + c) : ((row == g_idx[1]) ? (g_upd + D_ + c) : nullptr);
    uint32_t ov[4];
#pragma unroll
    for (int i = 0; i < 4; i++) {
        float b0 = bf_lo(na[i]), b1 = bf_hi(na[i]);
        if (up) { b0 = bf16r(b0 + up[2 * i]); b1 = bf16r(b1 + up[2 * i + 1]); }
        float t0 = bf16r(bf_lo(xa[i]) + bf16r(av[2 * i])), t1 = bf16r(bf_hi(xa[i]) + bf16r(av[2 * i + 1]));
        ov[i] = pack_bf16(t0 + b0, t1 + b1);
    }
    *reinterpret_cast<uint4*>(out + off) = make_uint4(ov[0], ov[1], ov[2], ov[3]);
}

constexpr int NRF = 44;
constexpr int RB = 272;
constexpr int SM_WSM = 0;
constexpr int SM_WO = SM_WSM + (64 - NRF) * 8 * 512;
constexpr int SM_PART = SM_WO + 22 * 8 * 512;
constexpr int SM_Q = SM_PART + 8 * 8 * 132 * 4;
constexpr int SM_K = SM_Q + 8 * RB;
constexpr int SM_V = SM_K + 40 * RB;
constexpr int SM_XBAR = SM_V + 48 * RB;
constexpr int SM_TOTAL = SM_XBAR + 16;
constexpr int SM_O = SM_PART;
constexpr int SM_S = SM_PART + 8 * RB;

__device__ __forceinline__ float4 ld_poll4(const float4* p) {
    float4 v;
    asm volatile("ld.relaxed.gpu.global.v4.f32 {%0,%1,%2,%3}, [%4];" : "=f"(v.x), "=f"(v.y), "=f"(v.z), "=f"(v.w) : "l"(p) : "memory");
    return v;
}
__device__ __forceinline__ unsigned ld_acquire(const unsigned* p) {
    unsigned v;
    asm volatile("ld.acquire.gpu.global.u32 %0, [%1];" : "=r"(v) : "l"(p) : "memory");
    return v;
}

__global__ void __cluster_dims__(3, 1, 1) __launch_bounds__(256, 1)
    rec_kernel(const bf16* __restrict__ Wq, const bf16* __restrict__ Wk, const bf16* __restrict__ Wv,
               const bf16* __restrict__ Wo) {
    extern __shared__ __align__(1024) uint8_t smem[];
    const uint32_t sb = smem_u32(smem);
    const int tid = threadIdx.x, w = tid >> 5, lane = tid & 31, g = lane >> 2, j = lane & 3;
    const uint32_t rank = cluster_ctarank();
    const int h = blockIdx.x / 3;
    const bf16* W = rank == 0 ? Wq : (rank == 1 ? Wk : Wv);
    const int tile0 = rank == 0 ? 0 : (rank == 1 ? 22 : 43);
    const int ntiles = rank == 0 ? 22 : 21;
    if (threadIdx.x == 0) atomicAdd(&g_resident[0], 1u);
    auto prefetch_kv = [&](int s) {
#pragma unroll
        for (int it = 0; it < 2; it++) {
            int idx = it * 256 + tid;
            int r = idx >> 4, ch = idx & 15;
            size_t off = (size_t)(s * SEG_ + r) * HD_ + h * DH_ + ch * 8;
            cp_async16(sb + SM_K + (8 + r) * RB + ch * 16, g_k + off);
            cp_async16(sb + SM_V + (8 + r) * RB + ch * 16, g_v + off);
        }
        cp_async_commit();
    };
    for (int i = tid; i < 8 * RB / 4; i += 256) *reinterpret_cast<uint32_t*>(smem + SM_V + 40 * RB + i * 4) = 0u;

    uint32_t wreg[NRF][4];
    {
        const int klo = 4 * (g >> 1) + (g & 1);
        const bf16* wbase = W + (size_t)(128 * w) * HD_ + h * DH_ + 2 * j;
#pragma unroll
        for (int f = 0; f < 64; f++) {
            const int i = f >> 3, mt = f & 7;
            const bf16* p = wbase + (size_t)(16 * i + klo) * HD_ + 16 * mt;
            uint32_t r0 = __ldg(reinterpret_cast<const uint32_t*>(p));
            uint32_t r1 = __ldg(reinterpret_cast<const uint32_t*>(p + 8));
            uint32_t r2 = __ldg(reinterpret_cast<const uint32_t*>(p + 2 * HD_));
            uint32_t r3 = __ldg(reinterpret_cast<const uint32_t*>(p + 2 * HD_ + 8));
            r0 = movm_t(r0); r1 = movm_t(r1); r2 = movm_t(r2); r3 = movm_t(r3);
            if (f < NRF) {
                wreg[f < NRF ? f : 0][0] = r0; wreg[f < NRF ? f : 0][1] = r1;
                wreg[f < NRF ? f : 0][2] = r2; wreg[f < NRF ? f : 0][3] = r3;
            } else {
                *reinterpret_cast<uint4*>(smem + SM_WSM + ((f - NRF) * 8 + w) * 512 + lane * 16) = make_uint4(r0, r1, r2, r3);
            }
        }
        for (int t = w; t < ntiles; t += 8) {
#pragma unroll
            for (int i = 0; i < 8; i++) {
                const bf16* p = Wo + (size_t)(h * DH_ + 16 * i + g) * D_ + (tile0 + t) * 16 + 4 * j;
                uint32_t r0 = __ldg(reinterpret_cast<const uint32_t*>(p));
                uint32_t r1 = __ldg(reinterpret_cast<const uint32_t*>(p + 2));
                uint32_t r2 = __ldg(reinterpret_cast<const uint32_t*>(p + 8 * D_));
                uint32_t r3 = __ldg(reinterpret_cast<const uint32_t*>(p + 8 * D_ + 2));
                r0 = movm_t(r0); r1 = movm_t(r1); r2 = movm_t(r2); r3 = movm_t(r3);
                *reinterpret_cast<uint4*>(smem + SM_WO + (t * 8 + i) * 512 + lane * 16) = make_uint4(r0, r1, r2, r3);
            }
        }
    }
    asm volatile("griddepcontrol.wait;" ::: "memory");
    prefetch_kv(0);
    if (tid == 0) {
        mbar_init(sb + SM_XBAR, 1);
        asm volatile("fence.mbarrier_init.release.cluster;" ::: "memory");
    }
    __syncthreads();
    cluster_arrive();
    cluster_wait();

    const uint32_t dst_local = sb + (rank == 0 ? SM_Q : (rank == 1 ? SM_K : SM_V)) + w * RB + lane * 8;
    const uint32_t dst0 = mapa(dst_local, 0), dst1 = mapa(dst_local, 1), dst2 = mapa(dst_local, 2);
    const uint32_t xb0 = mapa(sb + SM_XBAR, 0), xb1 = mapa(sb + SM_XBAR, 1), xb2 = mapa(sb + SM_XBAR, 2);
    const bool three = w + 16 < ntiles;
    const int ra = w <= 2 ? 0 : (w <= 5 ? 1 : 2);
    const int rb2 = (w == 2) ? 1 : ((w == 5) ? 2 : ra);
    const float scale = 0.08838834764831845f;

    for (int s = 0; s < NSEG_; s++) {
        if (tid == 0) mbar_expect_tx(sb + SM_XBAR, 3 * 2048);
        if (s > 0) {
            if (lane < 2) {
                const unsigned* cp = g_cnt + (s * 3 + (lane == 0 ? ra : rb2)) * 32;
                int guard = 0;
                unsigned v;
                do {
                    asm volatile("ld.relaxed.gpu.global.u32 %0, [%1];" : "=r"(v) : "l"(cp) : "memory");
                } while (v < 32u && ++guard < (1 << 22));
            }
            __syncwarp();
        }
        uint32_t bf[16];
        {
            const float4* mp = reinterpret_cast<const float4*>(g_memacc + (size_t)s * MT_ * D_ + (8 * w) * 128 + g * 16 + 4 * j);
            float4 mv[8];
#pragma unroll
            for (int i = 0; i < 8; i++) mv[i] = ld_poll4(mp + 32 * i);
#pragma unroll
            for (int i = 0; i < 8; i++) {
                bf[2 * i] = pack_bf16(mv[i].x, mv[i].y);
                bf[2 * i + 1] = pack_bf16(mv[i].z, mv[i].w);
            }
        }
        float acc[8][4];
#pragma unroll
        for (int mt = 0; mt < 8; mt++) acc[mt][0] = acc[mt][1] = acc[mt][2] = acc[mt][3] = 0.f;
#pragma unroll
        for (int i = 0; i < 8; i++) {
            const uint32_t b0 = bf[2 * i], b1 = bf[2 * i + 1];
#pragma unroll
            for (int mt = 0; mt < 8; mt++) {
                const int f = i * 8 + mt;
                if (f < NRF) {
                    mma16816(acc[mt], wreg[f < NRF ? f : 0][0], wreg[f < NRF ? f : 0][1], wreg[f < NRF ? f : 0][2],
                             wreg[f < NRF ? f : 0][3], b0, b1);
                } else {
                    uint4 a = *reinterpret_cast<const uint4*>(smem + SM_WSM + ((f - NRF) * 8 + w) * 512 + lane * 16);
                    mma16816(acc[mt], a.x, a.y, a.z, a.w, b0, b1);
                }
            }
        }
        {
            float* pp = reinterpret_cast<float*>(smem + SM_PART) + w * (8 * 132);
#pragma unroll
            for (int mt = 0; mt < 8; mt++) {
                pp[(2 * j) * 132 + 16 * mt + g] = acc[mt][0];
                pp[(2 * j + 1) * 132 + 16 * mt + g] = acc[mt][1];
                pp[(2 * j) * 132 + 16 * mt + g + 8] = acc[mt][2];
                pp[(2 * j + 1) * 132 + 16 * mt + g + 8] = acc[mt][3];
            }
        }
        cp_async_wait_all();
        __syncthreads();
        {
            const float* pp = reinterpret_cast<const float*>(smem + SM_PART) + w * 132 + 4 * lane;
            float4 t = *reinterpret_cast<const float4*>(pp);
#pragma unroll
            for (int q = 1; q < 8; q++) {
                float4 u = *reinterpret_cast<const float4*>(pp + q * (8 * 132));
                t.x += u.x; t.y += u.y; t.z += u.z; t.w += u.w;
            }
            const uint32_t lo = pack_bf16(t.x, t.y), hi = pack_bf16(t.z, t.w);
            asm volatile("st.async.weak.shared::cluster.mbarrier::complete_tx::bytes.v2.b32 [%0], {%1,%2}, [%3];" ::"r"(dst0), "r"(lo), "r"(hi), "r"(xb0) : "memory");
            asm volatile("st.async.weak.shared::cluster.mbarrier::complete_tx::bytes.v2.b32 [%0], {%1,%2}, [%3];" ::"r"(dst1), "r"(lo), "r"(hi), "r"(xb1) : "memory");
            asm volatile("st.async.weak.shared::cluster.mbarrier::complete_tx::bytes.v2.b32 [%0], {%1,%2}, [%3];" ::"r"(dst2), "r"(lo), "r"(hi), "r"(xb2) : "memory");
            if (rank != 0) {
                bf16* gp = (rank == 1 ? g_km : g_vm) + (size_t)(s * MT_ + w) * HD_ + h * DH_ + 4 * lane;
                *reinterpret_cast<uint2*>(gp) = make_uint2(lo, hi);
            }
        }
        uint4 wpre[8];
#pragma unroll
        for (int i = 0; i < 8; i++) wpre[i] = *reinterpret_cast<const uint4*>(smem + SM_WO + (w * 8 + i) * 512 + lane * 16);
        mbar_wait(sb + SM_XBAR, s & 1);
        if (s == NSEG_ - 1) break;
        if (w < 5) {
            float c0[4] = {0.f, 0.f, 0.f, 0.f}, c1[4] = {0.f, 0.f, 0.f, 0.f};
            const uint32_t qa = sb + SM_Q + (lane & 7) * RB + (lane >> 3) * 16;
            const uint32_t ka = sb + SM_K + (8 * w + (lane & 7)) * RB + (lane >> 3) * 16;
#pragma unroll
            for (int i2 = 0; i2 < 4; i2++) {
                uint32_t a0, a2, a0n, a2n, b0, b1, b0n, b1n;
                ldsm_x4(a0, a2, a0n, a2n, qa + i2 * 64);
                ldsm_x4(b0, b1, b0n, b1n, ka + i2 * 64);
                mma16816(c0, a0, 0u, a2, 0u, b0, b1);
                mma16816(c1, a0n, 0u, a2n, 0u, b0n, b1n);
            }
            float s0 = bf16r(bf16r(c0[0] + c1[0]) * scale), s1 = bf16r(bf16r(c0[1] + c1[1]) * scale);
            *reinterpret_cast<float2*>(smem + SM_S + (g * 40 + 8 * w + 2 * j) * 4) = make_float2(s0, s1);
        }
        __syncthreads();
        {
            const uint32_t va = sb + SM_V + (lane & 15) * RB + (16 * w + (lane >> 4) * 8) * 2;
            uint32_t vb[3][4];
#pragma unroll
            for (int i = 0; i < 3; i++) ldsm_x4_t(vb[i][0], vb[i][1], vb[i][2], vb[i][3], va + i * 16 * RB);
            float sv[5][2];
            float mx = -INFINITY;
#pragma unroll
            for (int t = 0; t < 5; t++) {
                float2 u = *reinterpret_cast<const float2*>(smem + SM_S + (g * 40 + 8 * t + 2 * j) * 4);
                sv[t][0] = u.x; sv[t][1] = u.y;
                mx = fmaxf(mx, fmaxf(u.x, u.y));
            }
            mx = fmaxf(mx, __shfl_xor_sync(0xffffffffu, mx, 1));
            mx = fmaxf(mx, __shfl_xor_sync(0xffffffffu, mx, 2));
            float sum = 0.f;
#pragma unroll
            for (int t = 0; t < 5; t++) {
                sv[t][0] = __expf(sv[t][0] - mx); sv[t][1] = __expf(sv[t][1] - mx);
                sum += sv[t][0] + sv[t][1];
            }
            sum += __shfl_xor_sync(0xffffffffu, sum, 1);
            sum += __shfl_xor_sync(0xffffffffu, sum, 2);
            const float inv = __frcp_rn(sum);
            uint32_t p[5];
#pragma unroll
            for (int t = 0; t < 5; t++) p[t] = pack_bf16(sv[t][0] * inv, sv[t][1] * inv);
            float o0[4] = {0.f, 0.f, 0.f, 0.f}, o1[4] = {0.f, 0.f, 0.f, 0.f};
            float o2[4] = {0.f, 0.f, 0.f, 0.f}, o3[4] = {0.f, 0.f, 0.f, 0.f};
            mma16816(o0, p[0], 0u, p[1], 0u, vb[0][0], vb[0][1]);
            mma16816(o1, p[0], 0u, p[1], 0u, vb[0][2], vb[0][3]);
            mma16816(o2, p[2], 0u, p[3], 0u, vb[1][0], vb[1][1]);
            mma16816(o3, p[2], 0u, p[3], 0u, vb[1][2], vb[1][3]);
            mma16816(o0, p[4], 0u, 0u, 0u, vb[2][0], vb[2][1]);
            mma16816(o1, p[4], 0u, 0u, 0u, vb[2][2], vb[2][3]);
            o0[0] += o2[0]; o0[1] += o2[1]; o1[0] += o3[0]; o1[1] += o3[1];
            *reinterpret_cast<uint32_t*>(smem + SM_O + g * RB + (16 * w + 2 * j) * 2) = pack_bf16(o0[0], o0[1]);
            *reinterpret_cast<uint32_t*>(smem + SM_O + g * RB + (16 * w + 8 + 2 * j) * 2) = pack_bf16(o1[0], o1[1]);
        }
        __syncthreads();
        {
            uint32_t ob[8][2];
            const uint32_t oa = sb + SM_O + (lane & 7) * RB + (lane >> 3) * 16;
#pragma unroll
            for (int i2 = 0; i2 < 4; i2++) ldsm_x4(ob[2 * i2][0], ob[2 * i2][1], ob[2 * i2 + 1][0], ob[2 * i2 + 1][1], oa + i2 * 64);
            float c0[3][4], c1[3][4];
#pragma unroll
            for (int q = 0; q < 3; q++)
#pragma unroll
                for (int e = 0; e < 4; e++) c0[q][e] = c1[q][e] = 0.f;
#pragma unroll
            for (int i = 0; i < 8; i += 2) {
                uint4 a = *reinterpret_cast<const uint4*>(smem + SM_WO + ((w + 8) * 8 + i) * 512 + lane * 16);
                uint4 a2 = *reinterpret_cast<const uint4*>(smem + SM_WO + ((w + 8) * 8 + i + 1) * 512 + lane * 16);
                mma16816(c0[0], wpre[i].x, wpre[i].y, wpre[i].z, wpre[i].w, ob[i][0], ob[i][1]);
                mma16816(c1[0], wpre[i + 1].x, wpre[i + 1].y, wpre[i + 1].z, wpre[i + 1].w, ob[i + 1][0], ob[i + 1][1]);
                mma16816(c0[1], a.x, a.y, a.z, a.w, ob[i][0], ob[i][1]);
                mma16816(c1[1], a2.x, a2.y, a2.z, a2.w, ob[i + 1][0], ob[i + 1][1]);
            }
            if (three) {
#pragma unroll
                for (int i = 0; i < 8; i += 2) {
                    uint4 a = *reinterpret_cast<const uint4*>(smem + SM_WO + ((w + 16) * 8 + i) * 512 + lane * 16);
                    uint4 a2 = *reinterpret_cast<const uint4*>(smem + SM_WO + ((w + 16) * 8 + i + 1) * 512 + lane * 16);
                    mma16816(c0[2], a.x, a.y, a.z, a.w, ob[i][0], ob[i][1]);
                    mma16816(c1[2], a2.x, a2.y, a2.z, a2.w, ob[i + 1][0], ob[i + 1][1]);
                }
            }
            const bool odd = g & 1;
            float* dp = g_memacc + (size_t)(s + 1) * MT_ * D_ + (tile0 + w) * 128 + (2 * j + (odd ? 1 : 0)) * 16 + 4 * (g >> 1);
#pragma unroll
            for (int q = 0; q < 3; q++) {
#pragma unroll
                for (int e = 0; e < 4; e++) c0[q][e] += c1[q][e];
                float r1 = __shfl_xor_sync(0xffffffffu, odd ? c0[q][0] : c0[q][1], 4);
                float r2 = __shfl_xor_sync(0xffffffffu, odd ? c0[q][2] : c0[q][3], 4);
                float v0 = odd ? r1 : c0[q][0], v1 = odd ? c0[q][1] : r1, v2 = odd ? r2 : c0[q][2], v3 = odd ? c0[q][3] : r2;
                if (q < 2 || three)
                    asm volatile("red.global.add.v4.f32 [%0], {%1,%2,%3,%4};" ::"l"(dp + q * 1024), "f"(v0), "f"(v1), "f"(v2), "f"(v3)
                                 : "memory");
            }
        }
        __syncthreads();
        if (tid == 0) {
            asm volatile("fence.acq_rel.gpu;" ::: "memory");
            asm volatile("red.relaxed.gpu.global.add.u32 [%0], 1;" ::"l"(g_cnt + ((s + 1) * 3 + rank) * 32) : "memory");
            if (rank != 0) asm volatile("red.relaxed.gpu.global.add.u32 [%0], 1;" ::"l"(g_prog + s * 32) : "memory");
        }
        prefetch_kv(s + 1);
    }
    __syncthreads();
    if (tid == 0 && rank != 0) {
        __threadfence();
        asm volatile("red.relaxed.gpu.global.add.u32 [%0], 1;" ::"l"(g_prog + (NSEG_ - 1) * 32) : "memory");
    }
    cluster_arrive();
    cluster_wait();
}

__global__ void gate_kernel(int seg) {
    int guard = 0;
    const unsigned* p = seg < 0 ? &g_resident[0] : g_prog + seg * 32;
    const unsigned target = seg < 0 ? 96u : 64u;
    while (ld_acquire(p) < target && ++guard < (1 << 22)) __nanosleep(200);
}

constexpr int AT_PAIR = (32 + 40 + 48) * RB;
__global__ void __launch_bounds__(128) attn_kernel(int seg0) {
    extern __shared__ __align__(1024) uint8_t smem[];
    const int tid = threadIdx.x, w = tid >> 5, lane = tid & 31, g = lane >> 2, j = lane & 3;
    const int pair = w >> 1, half = w & 1;
    const int unit = seg0 * 32 + blockIdx.x * 2 + pair;
    const int s = unit >> 5, h = unit & 31;
    if (tid == 0) {
        int guard = 0;
        while (ld_acquire(g_prog + s * 32) < 64u && ++guard < (1 << 22)) __nanosleep(400);
    }
    __syncthreads();
    uint8_t* base = smem + pair * AT_PAIR;
    const uint32_t sQ = smem_u32(base), sK = sQ + 32 * RB, sV = sK + 40 * RB;
    const int t64 = tid & 63;
    for (int idx = t64; idx < 112 * 16; idx += 64) {
        int r = idx >> 4, ch = idx & 15;
        const bf16* src;
        uint32_t dst;
        if (r < 32) {
            src = g_q + (size_t)(s * SEG_ + r) * HD_; dst = sQ + r * RB;
        } else if (r < 40) {
            src = g_km + (size_t)(s * MT_ + r - 32) * HD_; dst = sK + (r - 32) * RB;
        } else if (r < 72) {
            src = g_k + (size_t)(s * SEG_ + r - 40) * HD_; dst = sK + (r - 32) * RB;
        } else if (r < 80) {
            src = g_vm + (size_t)(s * MT_ + r - 72) * HD_; dst = sV + (r - 72) * RB;
        } else {
            src = g_v + (size_t)(s * SEG_ + r - 80) * HD_; dst = sV + (r - 72) * RB;
        }
        cp_async16(dst + ch * 16, src + h * DH_ + ch * 8);
    }
    cp_async_commit();
    for (int i = t64; i < 8 * RB / 4; i += 64) *reinterpret_cast<uint32_t*>(base + (32 + 40 + 40) * RB + i * 4) = 0u;
    cp_async_wait_all();
    __syncthreads();

    const float scale = 0.08838834764831845f;
    float sc[5][4];
#pragma unroll
    for (int t = 0; t < 5; t++) sc[t][0] = sc[t][1] = sc[t][2] = sc[t][3] = 0.f;
    const uint32_t qa = sQ + (16 * half + (lane & 15)) * RB + (lane >> 4) * 16;
    const uint32_t ka = sK + (lane & 7) * RB + (lane >> 3) * 16;
#pragma unroll
    for (int i2 = 0; i2 < 4; i2++) {
        uint32_t a[2][4];
        ldsm_x4(a[0][0], a[0][1], a[0][2], a[0][3], qa + i2 * 64);
        ldsm_x4(a[1][0], a[1][1], a[1][2], a[1][3], qa + i2 * 64 + 32);
#pragma unroll
        for (int t = 0; t < 5; t++) {
            uint32_t b0, b1, b2, b3;
            ldsm_x4(b0, b1, b2, b3, ka + t * 8 * RB + i2 * 64);
            mma16816(sc[t], a[0][0], a[0][1], a[0][2], a[0][3], b0, b1);
            mma16816(sc[t], a[1][0], a[1][1], a[1][2], a[1][3], b2, b3);
        }
    }
    const int r0 = 16 * half + g, r1 = r0 + 8;
    float m0 = -INFINITY, m1 = -INFINITY;
#pragma unroll
    for (int t = 0; t < 5; t++) {
#pragma unroll
        for (int e = 0; e < 2; e++) {
            const int kx = 8 * (t - 1) + 2 * j + e;
            float a = bf16r(bf16r(sc[t][e]) * scale), b = bf16r(bf16r(sc[t][2 + e]) * scale);
            if (t > 0 && kx > r0) a = -1e9f;
            if (t > 0 && kx > r1) b = -1e9f;
            sc[t][e] = a; sc[t][2 + e] = b;
            m0 = fmaxf(m0, a); m1 = fmaxf(m1, b);
        }
    }
    m0 = fmaxf(m0, __shfl_xor_sync(0xffffffffu, m0, 1)); m0 = fmaxf(m0, __shfl_xor_sync(0xffffffffu, m0, 2));
    m1 = fmaxf(m1, __shfl_xor_sync(0xffffffffu, m1, 1)); m1 = fmaxf(m1, __shfl_xor_sync(0xffffffffu, m1, 2));
    float l0 = 0.f, l1 = 0.f;
#pragma unroll
    for (int t = 0; t < 5; t++) {
#pragma unroll
        for (int e = 0; e < 2; e++) {
            sc[t][e] = __expf(sc[t][e] - m0); sc[t][2 + e] = __expf(sc[t][2 + e] - m1);
            l0 += sc[t][e]; l1 += sc[t][2 + e];
        }
    }
    l0 += __shfl_xor_sync(0xffffffffu, l0, 1); l0 += __shfl_xor_sync(0xffffffffu, l0, 2);
    l1 += __shfl_xor_sync(0xffffffffu, l1, 1); l1 += __shfl_xor_sync(0xffffffffu, l1, 2);
    const float i0 = 1.0f / l0, i1 = 1.0f / l1;
    uint32_t plo[5], phi[5];
#pragma unroll
    for (int t = 0; t < 5; t++) {
        plo[t] = pack_bf16(sc[t][0] * i0, sc[t][1] * i0);
        phi[t] = pack_bf16(sc[t][2] * i1, sc[t][3] * i1);
    }
    const uint32_t va = sV + (lane & 15) * RB + (lane >> 4) * 16;
    bf16* orow0 = g_o + (size_t)(s * SEG_ + r0) * HD_ + h * DH_ + 2 * j;
    bf16* orow1 = g_o + (size_t)(s * SEG_ + r1) * HD_ + h * DH_ + 2 * j;
#pragma unroll
    for (int n2 = 0; n2 < 8; n2++) {
        float o0[4] = {0.f, 0.f, 0.f, 0.f}, o1[4] = {0.f, 0.f, 0.f, 0.f};
#pragma unroll
        for (int i = 0; i < 3; i++) {
            uint32_t b00, b01, b10, b11;
            ldsm_x4_t(b00, b01, b10, b11, va + i * 16 * RB + n2 * 32);
            const uint32_t a0 = plo[2 * i], a1 = phi[2 * i];
            const uint32_t a2 = (i < 2) ? plo[i < 2 ? 2 * i + 1 : 0] : 0u, a3 = (i < 2) ? phi[i < 2 ? 2 * i + 1 : 0] : 0u;
            mma16816(o0, a0, a1, a2, a3, b00, b01);
            mma16816(o1, a0, a1, a2, a3, b10, b11);
        }
        *reinterpret_cast<uint32_t*>(orow0 + n2 * 16) = pack_bf16(o0[0], o0[1]);
        *reinterpret_cast<uint32_t*>(orow1 + n2 * 16) = pack_bf16(o0[2], o0[3]);
        *reinterpret_cast<uint32_t*>(orow0 + n2 * 16 + 8) = pack_bf16(o1[0], o1[1]);
        *reinterpret_cast<uint32_t*>(orow1 + n2 * 16 + 8) = pack_bf16(o1[2], o1[3]);
    }
}

typedef CUresult (*EncodeFn)(CUtensorMap*, CUtensorMapDataType, cuuint32_t, void*, const cuuint64_t*, const cuuint64_t*,
                             const cuuint32_t*, const cuuint32_t*, CUtensorMapInterleave, CUtensorMapSwizzle,
                             CUtensorMapL2promotion, CUtensorMapFloatOOBfill);

void make_map(EncodeFn fn, CUtensorMap* m, const void* ptr, uint64_t rows, uint64_t cols, uint32_t box_cols, uint32_t box_rows) {
    cuuint64_t dims[2] = {cols, rows};
    cuuint64_t strides[1] = {cols * 2};
    cuuint32_t box[2] = {box_cols, box_rows};
    cuuint32_t es[2] = {1, 1};
    fn(m, CU_TENSOR_MAP_DATA_TYPE_BFLOAT16, 2, const_cast<void*>(ptr), dims, strides, box, es, CU_TENSOR_MAP_INTERLEAVE_NONE,
       CU_TENSOR_MAP_SWIZZLE_128B, CU_TENSOR_MAP_L2_PROMOTION_L2_256B, CU_TENSOR_MAP_FLOAT_OOB_FILL_NONE);
}

struct HostState {
    bool init;
    const void* ptrs[4];
    CUtensorMap tmXn, tmWq, tmWk, tmWv, tmO, tmWo;
    EncodeFn fn;
    cudaStream_t side, side2;
    cudaEvent_t evFork, evJoin, evFfn, evQ, evJoin2;
};
HostState g_host;

}

extern "C" void kernel_launch(void* const* d_in, const int* in_sizes, int n_in, void* d_out, int out_size) {
    const bf16* A_x = (const bf16*)d_in[0];
    const bf16* A_mem0 = (const bf16*)d_in[1];
    const bf16* A_Wq = (const bf16*)d_in[2];
    const bf16* A_Wk = (const bf16*)d_in[3];
    const bf16* A_Wv = (const bf16*)d_in[4];
    const bf16* A_Wo = (const bf16*)d_in[5];
    const bf16* B_wr = (const bf16*)d_in[8];
    const bf16* B_wg = (const bf16*)d_in[9];
    const bf16* B_wu = (const bf16*)d_in[10];
    const bf16* B_wd = (const bf16*)d_in[11];
    bf16* out = (bf16*)d_out;

    constexpr int QKV_BN = 256, QKV_ST = 4, OUT_BN = 128, OUT_ST = 6;
    auto* qkv_fn = gemm_kernel<QKV_BN, QKV_ST, D_ / 64, 0>;
    auto* out_fn = gemm_kernel<OUT_BN, OUT_ST, HD_ / 64, 1>;
    auto* outsk_fn = gemm_kernel<OUT_BN, OUT_ST, HD_ / 64 / 4, 2>;

    HostState& hs = g_host;
    if (!hs.init) {
        void* fp = nullptr;
        cudaDriverEntryPointQueryResult qr;
        cudaGetDriverEntryPoint("cuTensorMapEncodeTiled", &fp, cudaEnableDefault, &qr);
        hs.fn = (EncodeFn)fp;
        cudaFuncSetAttribute(qkv_fn, cudaFuncAttributeMaxDynamicSharedMemorySize, GemmSmem<QKV_BN, QKV_ST>::TOTAL);
        cudaFuncSetAttribute(out_fn, cudaFuncAttributeMaxDynamicSharedMemorySize, GemmSmem<OUT_BN, OUT_ST>::TOTAL);
        cudaFuncSetAttribute(outsk_fn, cudaFuncAttributeMaxDynamicSharedMemorySize, GemmSmem<OUT_BN, OUT_ST>::TOTAL);
        cudaFuncSetAttribute(rec_kernel, cudaFuncAttributeMaxDynamicSharedMemorySize, SM_TOTAL);
        cudaFuncSetAttribute(attn_kernel, cudaFuncAttributeMaxDynamicSharedMemorySize, 2 * AT_PAIR);
        void *pxn, *po;
        cudaGetSymbolAddress(&pxn, g_xn);
        cudaGetSymbolAddress(&po, g_o);
        make_map(hs.fn, &hs.tmXn, pxn, S_, D_, 64, 128);
        make_map(hs.fn, &hs.tmO, po, S_, HD_, 64, 128);
        cudaStreamCreateWithFlags(&hs.side, cudaStreamNonBlocking);
        cudaStreamCreateWithFlags(&hs.side2, cudaStreamNonBlocking);
        cudaEventCreateWithFlags(&hs.evFfn, cudaEventDisableTiming);
        cudaEventCreateWithFlags(&hs.evQ, cudaEventDisableTiming);
        cudaEventCreateWithFlags(&hs.evJoin2, cudaEventDisableTiming);
        cudaEventCreateWithFlags(&hs.evFork, cudaEventDisableTiming);
        cudaEventCreateWithFlags(&hs.evJoin, cudaEventDisableTiming);
        hs.init = true;
    }
    if (hs.ptrs[0] != A_Wq || hs.ptrs[1] != A_Wk || hs.ptrs[2] != A_Wv || hs.ptrs[3] != A_Wo) {
        make_map(hs.fn, &hs.tmWq, A_Wq, D_, HD_, 64, 64);
        make_map(hs.fn, &hs.tmWk, A_Wk, D_, HD_, 64, 64);
        make_map(hs.fn, &hs.tmWv, A_Wv, D_, HD_, 64, 64);
        make_map(hs.fn, &hs.tmWo, A_Wo, HD_, D_, 64, 64);
        hs.ptrs[0] = A_Wq; hs.ptrs[1] = A_Wk; hs.ptrs[2] = A_Wv; hs.ptrs[3] = A_Wo;
    }

    constexpr int QKV_SM = GemmSmem<QKV_BN, QKV_ST>::TOTAL, OUT_SM = GemmSmem<OUT_BN, OUT_ST>::TOTAL;
    constexpr int NT = HD_ / QKV_BN;
    cudaStream_t mainS = cudaStreamPerThread, side = hs.side;
    ln_kernel<<<256, 256, 0, mainS>>>(A_x, B_wr, A_mem0);
    cudaEventRecord(hs.evFork, mainS);
    cudaStreamWaitEvent(side, hs.evFork, 0);
    cudaStreamWaitEvent(hs.side2, hs.evFork, 0);
    qkv_fn<<<dim3(16, 2 * NT), 384, QKV_SM, mainS>>>(hs.tmXn, hs.tmWq, hs.tmWk, hs.tmWv, nullptr, nullptr, NT, 0);
    {
        cudaLaunchConfig_t cfg = {};
        cfg.gridDim = dim3(96);
        cfg.blockDim = dim3(256);
        cfg.dynamicSmemBytes = SM_TOTAL;
        cfg.stream = mainS;
        cudaLaunchAttribute at[1];
        at[0].id = cudaLaunchAttributeProgrammaticStreamSerialization;
        at[0].val.programmaticStreamSerializationAllowed = 1;
        cfg.attrs = at;
        cfg.numAttrs = 1;
        cudaLaunchKernelEx(&cfg, rec_kernel, A_Wq, A_Wk, A_Wv, A_Wo);
    }
    ffn1_kernel<<<112, 256, 0, hs.side2>>>(B_wg, B_wu);
    ffn2_kernel<<<64, 256, 0, hs.side2>>>(B_wd);
    cudaEventRecord(hs.evFfn, hs.side2);
    gate_kernel<<<1, 1, 0, side>>>(-1);
    qkv_fn<<<dim3(16, NT), 384, QKV_SM, side>>>(hs.tmXn, hs.tmWq, hs.tmWk, hs.tmWv, nullptr, nullptr, 0, 0);
    cudaEventRecord(hs.evQ, side);
    {
        const int chunk_mt[4] = {4, 4, 3, 3};
        int mt0 = 0;
        for (int c = 0; c < 4; c++) {
            attn_kernel<<<chunk_mt[c] * 4 * H_ / 2, 128, 2 * AT_PAIR, side>>>(mt0 * 4);
            if (c == 0) cudaStreamWaitEvent(side, hs.evFfn, 0);
            out_fn<<<dim3(chunk_mt[c], D_ / OUT_BN), 384, OUT_SM, side>>>(hs.tmO, hs.tmWo, hs.tmWo, hs.tmWo, A_x, out, 0, mt0);
            mt0 += chunk_mt[c];
        }
    }
    cudaStreamWaitEvent(hs.side2, hs.evQ, 0);
    gate_kernel<<<1, 1, 0, hs.side2>>>(NSEG_ - 4);
    attn_kernel<<<8 * H_ / 2, 128, 2 * AT_PAIR, hs.side2>>>(NSEG_ - 8);
    outsk_fn<<<dim3(2, D_ / OUT_BN, 4), 384, OUT_SM, hs.side2>>>(hs.tmO, hs.tmWo, hs.tmWo, hs.tmWo, A_x, out, 0, 14);
    fin_kernel<<<256, 128, 0, hs.side2>>>(A_x, out, S_ - 256);
    cudaEventRecord(hs.evJoin, side);
    cudaEventRecord(hs.evJoin2, hs.side2);
    cudaStreamWaitEvent(mainS, hs.evJoin, 0);
    cudaStreamWaitEvent(mainS, hs.evJoin2, 0);
}
```
